```python
import torch

def _softmax(x, axis=-1):
    return torch.softmax(x, dim=axis)
def _gelu(x):
    return torch.nn.functional.gelu(x, approximate="tanh")
def _silu(x):
    return torch.nn.functional.silu(x)
def _sigmoid(x):
    return torch.sigmoid(x)
def _layernorm(x, axis=-1, eps=1e-5):
    m = x.mean(dim=axis, keepdim=True)
    v = x.var(dim=axis, keepdim=True, unbiased=False)
    return (x - m) / torch.sqrt(v + eps)
def _scatter_add(tgt, idx, src, axis=0):
    return tgt.clone().index_add_(axis, idx, src)
def _segment_sum(src, seg, n):
    out = torch.zeros((n,) + src.shape[1:], dtype=src.dtype)
    return out.index_add_(0, seg, src)
def _pad(x, pw):
    flat = tuple(v for pair in reversed(pw) for v in pair)
    return torch.nn.functional.pad(x, flat)

kernel_name = 'recurrent_scan__sliding_block_cached__dense_activation_relu__prompt'

def setup_inputs():

    _w = (lambda a: (lambda t: t.to(torch.bfloat16) if t.is_floating_point() else t)(torch.as_tensor(a)))
    def _A_setup():
        B, Sq, D = 1, 2048, 1024
        Hq, Hkv, Sk, Dh = 32, 4, 2048, 128
        assert Hq % Hkv == 0, (Hq, Hkv)
        return {
            "x": _w((lambda *s: torch.randn(*s, dtype=torch.bfloat16) * 0.05)(B, Sq, D)),
            "k_cache": _w((lambda *s: torch.randn(*s, dtype=torch.bfloat16) * 0.8)(B, Hkv, Sk, Dh)),
            "v_cache": _w((lambda *s: torch.randn(*s, dtype=torch.bfloat16) * 0.2)(B, Hkv, Sk, Dh)),
            "wq": _w((lambda *s: torch.randn(*s, dtype=torch.bfloat16) * 0.8)(D, Hq * Dh) * (D ** -0.5)),
            "wo": _w((lambda *s: torch.randn(*s, dtype=torch.bfloat16) * 0.2)(Hq * Dh, D) * ((Hq * Dh) ** -0.5)),
        }
    _A_in = _A_setup()

    def _B_setup():
        B, S, D, Dff = 1, 2048, 1024, 3584
        return {
            "x": _w((lambda *s: torch.randn(*s, dtype=torch.bfloat16) * 0.05)(B, S, D)),
            "w1": _w((lambda *s: torch.randn(*s, dtype=torch.bfloat16) * 0.1)(D, Dff)),
            "w2": _w((lambda *s: torch.randn(*s, dtype=torch.bfloat16) * 0.1)(Dff, D)),
        }
    _B_in = _B_setup()

    return {
        "A_x": _A_in["x"],
        "A_k_cache": _A_in["k_cache"],
        "A_v_cache": _A_in["v_cache"],
        "A_wq": _A_in["wq"],
        "A_wo": _A_in["wo"],
        "B_x": _B_in["x"],
        "B_w1": _B_in["w1"],
        "B_w2": _B_in["w2"],
    }

def reference(A_x, A_k_cache, A_v_cache, A_wq, A_wo, B_x, B_w1, B_w2):
    def _A_ref(x, k_cache, v_cache, wq, wo):
        B, Sq, D = x.shape
        Hq, Dh = 32, 128
        Hkv, Sk = k_cache.shape[1], k_cache.shape[2]
        W = min(4096, max(256, Sk // 4))
        rep = Hq // Hkv
        q = (lambda x, *d: x.permute(*d))((x @ wq).reshape(B, Sq, Hq, Dh), 0, 2, 1, 3)
        k = (lambda x, n, axis: torch.repeat_interleave(x, n, dim=axis))(k_cache[:, :, Sk - W:, :], rep, axis=1)
        v = (lambda x, n, axis: torch.repeat_interleave(x, n, dim=axis))(v_cache[:, :, Sk - W:, :], rep, axis=1)
        scores = torch.einsum("bhqd,bhkd->bhqk", q, k) * (Dh ** -0.5)
        p = _softmax(scores, axis=-1)
        o = torch.einsum("bhqk,bhkd->bhqd", p, v)
        return (lambda x, *d: x.permute(*d))(o, 0, 2, 1, 3).reshape(B, Sq, Hq * Dh) @ wo

    def _B_ref(x, w1, w2):
        h = torch.einsum("bsd,df->bsf", x, w1)
        zero = torch.zeros_like(h)
        h = torch.maximum(h, zero)
        return torch.einsum("bsf,fd->bsd", h, w2)

    x = A_x
    xn = _layernorm(x, axis=-1)
    s = _A_ref(xn, A_k_cache, A_v_cache, A_wq, A_wo)
    g = _silu(_B_ref(xn, B_w1, B_w2))
    return x + s * g
```

```cpp
#include <cuda_runtime.h>
#include <cuda_bf16.h>
#include <cuda.h>
#include <stdint.h>

#define GEMM_TURNS 1
#define ATT_TURNS 1
#define ATT_SYNC(w) turn_sync(w)
#define ATT_ARRIVE(w) turn_arrive(w)
#define ZERO_LEAD 14
#define HELD_K 4
namespace {

constexpr int S_ROWS = 2048, D_MODEL = 1024, DFF = 3584, SK = 2048, WIN = 512;
constexpr int C_XN = 0, C_O = 1024, C_H = 5120, C_XQ = 8704, C_X = 9728, S_COLS = 10752;
constexpr int NSTAGE = 4, STAGE_BYTES = 49152, A_BYTES = 16384;
constexpr int SMEM_STG = NSTAGE * STAGE_BYTES;
constexpr int SMEM_BAR = SMEM_STG + 32768;
constexpr int SMEM_CS = SMEM_BAR + 256;
constexpr int SMEM_STAT = SMEM_CS + 1024;
constexpr int SMEM_OWN = SMEM_STAT + 1024;
constexpr int SMEM_TOTAL = SMEM_OWN + 128 + 64;
constexpr int NCTA = 128;
constexpr float SM_SCALE = 0.08838834764831845f * 1.4426950408889634f;
constexpr int F_LN = 0, F_O = 16, F_HA = 32, F_HB1 = 48, F_HB2 = 64, F_ST = 80, F_CS = 96, F_KV = 104, F_DONE = 108, F_X = 109, NFLAGS = 109 + NCTA;

__device__ __nv_bfloat16 g_scratch[(size_t)S_ROWS * S_COLS];
struct __align__(1024) SyncArea {
  unsigned flags[NFLAGS * 32];
  float2 stats[S_ROWS];
  float colsum[8 * 256];
  unsigned long long kvmax[4 * 2 * 16];
};
__device__ SyncArea g_sync;
#define g_flags g_sync.flags
#define PROF(slot) do {} while (0)
#define APROF(k) do {} while (0)
#define HPROF(k) do {} while (0)
#define PROFG(slot) do {} while (0)

struct Maps {
  CUtensorMap s_ld, s_st, wq, w1a, w1b, wo, w2, k, v, x_ld, out_st, wq_cs;
};

__device__ __forceinline__ uint32_t smem_u32(const void* p) { return (uint32_t)__cvta_generic_to_shared(p); }
__device__ __forceinline__ void mbar_init(uint32_t bar, uint32_t cnt) { asm volatile("mbarrier.init.shared::cta.b64 [%0], %1;" :: "r"(bar), "r"(cnt)); }
__device__ __forceinline__ void mbar_expect_tx(uint32_t bar, uint32_t bytes) { asm volatile("mbarrier.arrive.expect_tx.shared::cta.b64 _, [%0], %1;" :: "r"(bar), "r"(bytes) : "memory"); }
__device__ __forceinline__ void mbar_arrive(uint32_t bar) { asm volatile("mbarrier.arrive.shared::cta.b64 _, [%0];" :: "r"(bar) : "memory"); }
__device__ __forceinline__ void mbar_wait(uint32_t bar, uint32_t parity) {
  asm volatile("{\n.reg .pred p;\n.reg .u32 c;\n"
    "mbarrier.try_wait.parity.shared::cta.b64 p, [%0], %1;\n"
    "@p bra DONE;\n"
    "mov.u32 c, 0;\n"
    "WAIT:\n"
    "mbarrier.try_wait.parity.shared::cta.b64 p, [%0], %1;\n"
    "@p bra DONE;\n"
    "add.u32 c, c, 1;\n"
    "setp.gt.u32 p, c, 0x80000;\n"
    "@p trap;\n"
    "bra WAIT;\n"
    "DONE:\n}" :: "r"(bar), "r"(parity) : "memory");
}
__device__ __forceinline__ void tma_load_2d(uint32_t dst, const CUtensorMap* m, uint32_t bar, int c0, int c1) {
  asm volatile("cp.async.bulk.tensor.2d.shared::cluster.global.mbarrier::complete_tx::bytes [%0], [%1, {%3, %4}], [%2];"
    :: "r"(dst), "l"(m), "r"(bar), "r"(c0), "r"(c1) : "memory");
}
__device__ __forceinline__ void tma_load_2d_mc(uint32_t dst, const CUtensorMap* m, uint32_t bar, int c0, int c1) {
  asm volatile("cp.async.bulk.tensor.2d.shared::cluster.global.mbarrier::complete_tx::bytes.multicast::cluster [%0], [%1, {%3, %4}], [%2], %5;"
    :: "r"(dst), "l"(m), "r"(bar), "r"(c0), "r"(c1), "h"((uint16_t)3) : "memory");
}
__device__ __forceinline__ void tma_load_3d_mc(uint32_t dst, const CUtensorMap* m, uint32_t bar, int c0, int c1, int c2) {
  asm volatile("cp.async.bulk.tensor.3d.shared::cluster.global.mbarrier::complete_tx::bytes.multicast::cluster [%0], [%1, {%3, %4, %5}], [%2], %6;"
    :: "r"(dst), "l"(m), "r"(bar), "r"(c0), "r"(c1), "r"(c2), "h"((uint16_t)3) : "memory");
}
__device__ __forceinline__ void tma_store_2d(const CUtensorMap* m, uint32_t src, int c0, int c1) {
  asm volatile("cp.async.bulk.tensor.2d.global.shared::cta.bulk_group [%0, {%2, %3}], [%1];"
    :: "l"(m), "r"(src), "r"(c0), "r"(c1) : "memory");
}
__device__ __forceinline__ void bulk_commit() { asm volatile("cp.async.bulk.commit_group;" ::: "memory"); }
__device__ __forceinline__ void bulk_wait_read0() { asm volatile("cp.async.bulk.wait_group.read 0;" ::: "memory"); }
__device__ __forceinline__ void bulk_wait0() { asm volatile("cp.async.bulk.wait_group 0;" ::: "memory"); }
__device__ __forceinline__ void fence_async_smem() { asm volatile("fence.proxy.async.shared::cta;" ::: "memory"); }
__device__ __forceinline__ void wg_fence() { asm volatile("wgmma.fence.sync.aligned;" ::: "memory"); }
__device__ __forceinline__ void wg_commit() { asm volatile("wgmma.commit_group.sync.aligned;" ::: "memory"); }
template<int N> __device__ __forceinline__ void wg_wait() { asm volatile("wgmma.wait_group.sync.aligned %0;" :: "n"(N) : "memory"); }
__device__ __forceinline__ uint32_t desc_lo(uint32_t addr, uint32_t lbo) { return ((addr & 0x3FFFF) >> 4) | ((lbo >> 4) << 16); }
template<int N, int CNT = N> __device__ __forceinline__ void reg_fence(float (&d)[N]) {
  #pragma unroll
  for (int i = 0; i < CNT; i++) asm volatile("" : "+f"(d[i]) :: "memory");
}
template<int N> __device__ __forceinline__ void reg_fence(uint32_t (&d)[N]) {
  #pragma unroll
  for (int i = 0; i < N; i++) asm volatile("" : "+r"(d[i]) :: "memory");
}
template<int N> __device__ __forceinline__ void reg_define(float (&d)[N]) {
  #pragma unroll
  for (int i = 0; i < N; i++) asm volatile("" : "=f"(d[i]));
}
__device__ __forceinline__ void flag_signal(int f) { asm volatile("red.release.gpu.global.add.u32 [%0], 1;" :: "l"(g_flags + f * 32) : "memory"); }
__device__ __forceinline__ void flag_wait(int f, unsigned target) {
  asm volatile("{\n.reg .pred p;\n.reg .u32 c, v;\nmov.u32 c, 0;\n"
    "WAIT:\n"
    "ld.acquire.gpu.global.u32 v, [%0];\n"
    "sub.u32 v, v, %1;\n"
    "setp.ge.s32 p, v, 0;\n"
    "@p bra DONE;\n"
    "add.u32 c, c, 1;\n"
    "setp.gt.u32 p, c, 0x400000;\n"
    "@p trap;\n"
    "bra WAIT;\n"
    "DONE:\n"
    "fence.proxy.async.global;\n}" :: "l"(g_flags + f * 32), "r"(target) : "memory");
}
__device__ __forceinline__ uint32_t pack_bf16(float lo, float hi) { uint32_t r; asm("cvt.rn.bf16x2.f32 %0, %1, %2;" : "=r"(r) : "f"(hi), "f"(lo)); return r; }
__device__ __forceinline__ uint32_t pack_bf16_relu(float lo, float hi) { uint32_t r; asm("cvt.rn.relu.bf16x2.f32 %0, %1, %2;" : "=r"(r) : "f"(hi), "f"(lo)); return r; }
__device__ __forceinline__ float bf_lo(uint32_t v) { return __uint_as_float(v << 16); }
__device__ __forceinline__ float bf_hi(uint32_t v) { return __uint_as_float(v & 0xffff0000u); }
__device__ __forceinline__ float round_bf16(float x) { return bf_lo(pack_bf16(x, x)); }
__device__ __forceinline__ uint32_t bf2_sub(uint32_t a, uint32_t b) { uint32_t r; asm("sub.rn.bf16x2 %0, %1, %2;" : "=r"(r) : "r"(a), "r"(b)); return r; }
__device__ __forceinline__ uint32_t bf2_add(uint32_t a, uint32_t b) { uint32_t r; asm("add.rn.bf16x2 %0, %1, %2;" : "=r"(r) : "r"(a), "r"(b)); return r; }
__device__ __forceinline__ uint32_t bf2_mul(uint32_t a, uint32_t b) { uint32_t r; asm("mul.rn.bf16x2 %0, %1, %2;" : "=r"(r) : "r"(a), "r"(b)); return r; }
__device__ __forceinline__ uint32_t bf2_fma(uint32_t a, uint32_t b, uint32_t c) { uint32_t r; asm("fma.rn.bf16x2 %0, %1, %2, %3;" : "=r"(r) : "r"(a), "r"(b), "r"(c)); return r; }
__device__ __forceinline__ float ex2(float x) { float r; asm("ex2.approx.ftz.f32 %0, %1;" : "=f"(r) : "f"(x)); return r; }
__device__ __forceinline__ float rcp(float x) { float r; asm("rcp.approx.ftz.f32 %0, %1;" : "=f"(r) : "f"(x)); return r; }
__device__ __forceinline__ void stsm_x4(uint32_t addr, uint32_t r0, uint32_t r1, uint32_t r2, uint32_t r3) {
  asm volatile("stmatrix.sync.aligned.m8n8.x4.shared.b16 [%0], {%1, %2, %3, %4};" :: "r"(addr), "r"(r0), "r"(r1), "r"(r2), "r"(r3) : "memory");
}
__device__ __forceinline__ void ldsm_x4(uint32_t addr, uint32_t& r0, uint32_t& r1, uint32_t& r2, uint32_t& r3) {
  asm volatile("ldmatrix.sync.aligned.m8n8.x4.shared.b16 {%0, %1, %2, %3}, [%4];" : "=r"(r0), "=r"(r1), "=r"(r2), "=r"(r3) : "r"(addr) : "memory");
}

template<int TB> __device__ __forceinline__ void wgmma_ss_n256(float (&d)[128], uint32_t descA, uint32_t descB, int scaleD) {
  asm volatile("{\n.reg .pred p;\n.reg .b64 da, db;\nmov.b64 da, {%128, 0x40000040};\nmov.b64 db, {%129, 0x40000040};\nsetp.ne.b32 p, %130, 0;\n"
    "wgmma.mma_async.sync.aligned.m64n256k16.f32.bf16.bf16 {"
    "%0, %1, %2, %3, %4, %5, %6, %7, %8, %9, %10, %11, %12, %13, %14, %15, "
    "%16, %17, %18, %19, %20, %21, %22, %23, %24, %25, %26, %27, %28, %29, %30, %31, "
    "%32, %33, %34, %35, %36, %37, %38, %39, %40, %41, %42, %43, %44, %45, %46, %47, "
    "%48, %49, %50, %51, %52, %53, %54, %55, %56, %57, %58, %59, %60, %61, %62, %63, "
    "%64, %65, %66, %67, %68, %69, %70, %71, %72, %73, %74, %75, %76, %77, %78, %79, "
    "%80, %81, %82, %83, %84, %85, %86, %87, %88, %89, %90, %91, %92, %93, %94, %95, "
    "%96, %97, %98, %99, %100, %101, %102, %103, %104, %105, %106, %107, %108, %109, %110, %111, "
    "%112, %113, %114, %115, %116, %117, %118, %119, %120, %121, %122, %123, %124, %125, %126, %127"
    "}, da, db, p, 1, 1, 0, %131;\n}\n"
    : "+f"(d[0]), "+f"(d[1]), "+f"(d[2]), "+f"(d[3]), "+f"(d[4]), "+f"(d[5]), "+f"(d[6]), "+f"(d[7]), "+f"(d[8]), "+f"(d[9]), "+f"(d[10]),
      "+f"(d[11]), "+f"(d[12]), "+f"(d[13]), "+f"(d[14]), "+f"(d[15]), "+f"(d[16]), "+f"(d[17]), "+f"(d[18]), "+f"(d[19]), "+f"(d[20]), "+f"(d[21]),
      "+f"(d[22]), "+f"(d[23]), "+f"(d[24]), "+f"(d[25]), "+f"(d[26]), "+f"(d[27]), "+f"(d[28]), "+f"(d[29]), "+f"(d[30]), "+f"(d[31]), "+f"(d[32]),
      "+f"(d[33]), "+f"(d[34]), "+f"(d[35]), "+f"(d[36]), "+f"(d[37]), "+f"(d[38]), "+f"(d[39]), "+f"(d[40]), "+f"(d[41]), "+f"(d[42]), "+f"(d[43]),
      "+f"(d[44]), "+f"(d[45]), "+f"(d[46]), "+f"(d[47]), "+f"(d[48]), "+f"(d[49]), "+f"(d[50]), "+f"(d[51]), "+f"(d[52]), "+f"(d[53]), "+f"(d[54]),
      "+f"(d[55]), "+f"(d[56]), "+f"(d[57]), "+f"(d[58]), "+f"(d[59]), "+f"(d[60]), "+f"(d[61]), "+f"(d[62]), "+f"(d[63]), "+f"(d[64]), "+f"(d[65]),
      "+f"(d[66]), "+f"(d[67]), "+f"(d[68]), "+f"(d[69]), "+f"(d[70]), "+f"(d[71]), "+f"(d[72]), "+f"(d[73]), "+f"(d[74]), "+f"(d[75]), "+f"(d[76]),
      "+f"(d[77]), "+f"(d[78]), "+f"(d[79]), "+f"(d[80]), "+f"(d[81]), "+f"(d[82]), "+f"(d[83]), "+f"(d[84]), "+f"(d[85]), "+f"(d[86]), "+f"(d[87]),
      "+f"(d[88]), "+f"(d[89]), "+f"(d[90]), "+f"(d[91]), "+f"(d[92]), "+f"(d[93]), "+f"(d[94]), "+f"(d[95]), "+f"(d[96]), "+f"(d[97]), "+f"(d[98]),
      "+f"(d[99]), "+f"(d[100]), "+f"(d[101]), "+f"(d[102]), "+f"(d[103]), "+f"(d[104]), "+f"(d[105]), "+f"(d[106]), "+f"(d[107]), "+f"(d[108]),
      "+f"(d[109]), "+f"(d[110]), "+f"(d[111]), "+f"(d[112]), "+f"(d[113]), "+f"(d[114]), "+f"(d[115]), "+f"(d[116]), "+f"(d[117]), "+f"(d[118]),
      "+f"(d[119]), "+f"(d[120]), "+f"(d[121]), "+f"(d[122]), "+f"(d[123]), "+f"(d[124]), "+f"(d[125]), "+f"(d[126]), "+f"(d[127])
    : "r"(descA), "r"(descB), "r"(scaleD), "n"(TB));
}
template<int TB> __device__ __forceinline__ void wgmma_ss_n192(float (&d)[128], uint32_t descA, uint32_t descB, int scaleD) {
  asm volatile("{\n.reg .pred p;\n.reg .b64 da, db;\nmov.b64 da, {%96, 0x40000040};\nmov.b64 db, {%97, 0x40000040};\nsetp.ne.b32 p, %98, 0;\n"
    "wgmma.mma_async.sync.aligned.m64n192k16.f32.bf16.bf16 {"
    "%0, %1, %2, %3, %4, %5, %6, %7, %8, %9, %10, %11, %12, %13, %14, %15, "
    "%16, %17, %18, %19, %20, %21, %22, %23, %24, %25, %26, %27, %28, %29, %30, %31, "
    "%32, %33, %34, %35, %36, %37, %38, %39, %40, %41, %42, %43, %44, %45, %46, %47, "
    "%48, %49, %50, %51, %52, %53, %54, %55, %56, %57, %58, %59, %60, %61, %62, %63, "
    "%64, %65, %66, %67, %68, %69, %70, %71, %72, %73, %74, %75, %76, %77, %78, %79, "
    "%80, %81, %82, %83, %84, %85, %86, %87, %88, %89, %90, %91, %92, %93, %94, %95"
    "}, da, db, p, 1, 1, 0, %99;\n}\n"
    : "+f"(d[0]), "+f"(d[1]), "+f"(d[2]), "+f"(d[3]), "+f"(d[4]), "+f"(d[5]), "+f"(d[6]), "+f"(d[7]), "+f"(d[8]), "+f"(d[9]), "+f"(d[10]),
      "+f"(d[11]), "+f"(d[12]), "+f"(d[13]), "+f"(d[14]), "+f"(d[15]), "+f"(d[16]), "+f"(d[17]), "+f"(d[18]), "+f"(d[19]), "+f"(d[20]), "+f"(d[21]),
      "+f"(d[22]), "+f"(d[23]), "+f"(d[24]), "+f"(d[25]), "+f"(d[26]), "+f"(d[27]), "+f"(d[28]), "+f"(d[29]), "+f"(d[30]), "+f"(d[31]), "+f"(d[32]),
      "+f"(d[33]), "+f"(d[34]), "+f"(d[35]), "+f"(d[36]), "+f"(d[37]), "+f"(d[38]), "+f"(d[39]), "+f"(d[40]), "+f"(d[41]), "+f"(d[42]), "+f"(d[43]),
      "+f"(d[44]), "+f"(d[45]), "+f"(d[46]), "+f"(d[47]), "+f"(d[48]), "+f"(d[49]), "+f"(d[50]), "+f"(d[51]), "+f"(d[52]), "+f"(d[53]), "+f"(d[54]),
      "+f"(d[55]), "+f"(d[56]), "+f"(d[57]), "+f"(d[58]), "+f"(d[59]), "+f"(d[60]), "+f"(d[61]), "+f"(d[62]), "+f"(d[63]), "+f"(d[64]), "+f"(d[65]),
      "+f"(d[66]), "+f"(d[67]), "+f"(d[68]), "+f"(d[69]), "+f"(d[70]), "+f"(d[71]), "+f"(d[72]), "+f"(d[73]), "+f"(d[74]), "+f"(d[75]), "+f"(d[76]),
      "+f"(d[77]), "+f"(d[78]), "+f"(d[79]), "+f"(d[80]), "+f"(d[81]), "+f"(d[82]), "+f"(d[83]), "+f"(d[84]), "+f"(d[85]), "+f"(d[86]), "+f"(d[87]),
      "+f"(d[88]), "+f"(d[89]), "+f"(d[90]), "+f"(d[91]), "+f"(d[92]), "+f"(d[93]), "+f"(d[94]), "+f"(d[95])
    : "r"(descA), "r"(descB), "r"(scaleD), "n"(TB));
}
template<int TB> __device__ __forceinline__ void wgmma_rs_n128(float (&d)[64], uint32_t a0, uint32_t a1, uint32_t a2, uint32_t a3, uint32_t descB, int scaleD) {
  asm volatile("{\n.reg .pred p;\n.reg .b64 db;\nmov.b64 db, {%68, 0x40000040};\nsetp.ne.b32 p, %69, 0;\n"
    "wgmma.mma_async.sync.aligned.m64n128k16.f32.bf16.bf16 {"
    "%0, %1, %2, %3, %4, %5, %6, %7, %8, %9, %10, %11, %12, %13, %14, %15, "
    "%16, %17, %18, %19, %20, %21, %22, %23, %24, %25, %26, %27, %28, %29, %30, %31, "
    "%32, %33, %34, %35, %36, %37, %38, %39, %40, %41, %42, %43, %44, %45, %46, %47, "
    "%48, %49, %50, %51, %52, %53, %54, %55, %56, %57, %58, %59, %60, %61, %62, %63"
    "}, {%64, %65, %66, %67}, db, p, 1, 1, %70;\n}\n"
    : "+f"(d[0]), "+f"(d[1]), "+f"(d[2]), "+f"(d[3]), "+f"(d[4]), "+f"(d[5]), "+f"(d[6]), "+f"(d[7]), "+f"(d[8]), "+f"(d[9]), "+f"(d[10]),
      "+f"(d[11]), "+f"(d[12]), "+f"(d[13]), "+f"(d[14]), "+f"(d[15]), "+f"(d[16]), "+f"(d[17]), "+f"(d[18]), "+f"(d[19]), "+f"(d[20]), "+f"(d[21]),
      "+f"(d[22]), "+f"(d[23]), "+f"(d[24]), "+f"(d[25]), "+f"(d[26]), "+f"(d[27]), "+f"(d[28]), "+f"(d[29]), "+f"(d[30]), "+f"(d[31]), "+f"(d[32]),
      "+f"(d[33]), "+f"(d[34]), "+f"(d[35]), "+f"(d[36]), "+f"(d[37]), "+f"(d[38]), "+f"(d[39]), "+f"(d[40]), "+f"(d[41]), "+f"(d[42]), "+f"(d[43]),
      "+f"(d[44]), "+f"(d[45]), "+f"(d[46]), "+f"(d[47]), "+f"(d[48]), "+f"(d[49]), "+f"(d[50]), "+f"(d[51]), "+f"(d[52]), "+f"(d[53]), "+f"(d[54]),
      "+f"(d[55]), "+f"(d[56]), "+f"(d[57]), "+f"(d[58]), "+f"(d[59]), "+f"(d[60]), "+f"(d[61]), "+f"(d[62]), "+f"(d[63])
    : "r"(a0), "r"(a1), "r"(a2), "r"(a3), "r"(descB), "r"(scaleD), "n"(TB));
}

struct Pipe {
  int st; uint32_t ph;
  __device__ __forceinline__ void next() { if (++st == NSTAGE) { st = 0; ph ^= 1; } }
};

struct Ctx {
  uint32_t base;
  uint32_t full0, sfull, sempty;
  uint32_t stg;
  uint32_t sw[4];
  int w, lane, warp;
  int njob;
  bool elect;
  bool rel;
  uint32_t relbar;
  __device__ __forceinline__ void release(int st) const {
    if (rel) asm volatile("mbarrier.arrive.shared::cluster.b64 _, [%0];" :: "r"(relbar + st * 8) : "memory");
  }
};

__device__ __forceinline__ void turn_sync(int w) { asm volatile("bar.sync %0, 256;" :: "r"(1 + w) : "memory"); }
__device__ __forceinline__ void turn_arrive(int w) { asm volatile("bar.arrive %0, 256;" :: "r"(2 - w) : "memory"); }

__device__ __forceinline__ void stg_acquire(const Ctx& c) { mbar_wait(c.sempty, (c.njob & 1) ^ 1); }
__device__ __forceinline__ void stg_publish(Ctx& c) {
  fence_async_smem();
  __syncwarp();
  if (c.lane == 0) mbar_arrive(c.sfull);
  c.njob++;
}
template<int NBOX>
__device__ __forceinline__ void stg_store(const uint32_t* r, Ctx& c) {
  stg_acquire(c);
  #pragma unroll
  for (int q = 0; q < 4 * NBOX; q++) stsm_x4(c.stg + (q >> 2) * 8192 + c.sw[q & 3], r[4 * q], r[4 * q + 1], r[4 * q + 2], r[4 * q + 3]);
  stg_publish(c);
}

template<int N, bool FIRST>
__device__ __forceinline__ void gemm_kblock(float (&acc)[128], const Ctx& c, const Pipe& p) {
  mbar_wait(c.full0 + p.st * 8, p.ph);
  const uint32_t sa = c.base + p.st * STAGE_BYTES;
  const uint32_t da = desc_lo(sa + c.w * 8192, 16), db = desc_lo(sa + A_BYTES, 4096);
  turn_sync(c.w);
  wg_fence();
  #pragma unroll
  for (int kk = 0; kk < 4; kk++) {
    if (N == 256) wgmma_ss_n256<1>(acc, da + kk * 2, db + (kk >> 1) * 1024 + (kk & 1) * 128, !(FIRST && kk == 0));
    else          wgmma_ss_n192<1>(acc, da + kk * 2, db + (kk >> 1) * 1024 + (kk & 1) * 128, !(FIRST && kk == 0));
  }
  wg_commit();
  turn_arrive(c.w);
}
template<int N, int HELD, bool LAST = false>
__device__ __forceinline__ void gemm_tile(float (&acc)[128], uint32_t (&held)[32], Ctx& c, Pipe& p, int nk) {
  reg_define(acc);
  gemm_kblock<N, true>(acc, c, p);
  int prev = p.st;
  p.next();
  #pragma unroll 1
  for (int k = 1; k < nk; k++) {
    gemm_kblock<N, false>(acc, c, p);
    if (HELD > 0 && k == HELD_K) stg_store<HELD>(held, c);
    wg_wait<1>();
    if (!LAST || k <= nk - NSTAGE + 1) c.release(prev);
    prev = p.st;
    p.next();
  }
  wg_wait<0>();
  if (!LAST) c.release(prev);
  reg_fence<128, N / 2>(acc);
}

template<int NBOX>
__device__ __forceinline__ void epi_relu(float (&acc)[128], uint32_t (&held)[32], Ctx& c) {
  uint32_t r[32];
  #pragma unroll
  for (int i = 0; i < 32; i++) r[i] = pack_bf16_relu(acc[2 * i], acc[2 * i + 1]);
  stg_store<2>(r, c);
  #pragma unroll
  for (int i = 0; i < 16 * (NBOX - 2); i++) held[i] = pack_bf16_relu(acc[64 + 2 * i], acc[65 + 2 * i]);
}

__device__ __forceinline__ void o_store(float (&O)[64], float l0, float l1, Ctx& c) {
  l0 += __shfl_xor_sync(0xffffffffu, l0, 1); l1 += __shfl_xor_sync(0xffffffffu, l1, 1);
  l0 += __shfl_xor_sync(0xffffffffu, l0, 2); l1 += __shfl_xor_sync(0xffffffffu, l1, 2);
  const float i0 = rcp(l0), i1 = rcp(l1);
  stg_acquire(c);
  #pragma unroll
  for (int q = 0; q < 8; q++)
    stsm_x4(c.stg + (q >> 2) * 8192 + c.sw[q & 3], pack_bf16(O[8 * q] * i0, O[8 * q + 1] * i0), pack_bf16(O[8 * q + 2] * i1, O[8 * q + 3] * i1),
            pack_bf16(O[8 * q + 4] * i0, O[8 * q + 5] * i0), pack_bf16(O[8 * q + 6] * i1, O[8 * q + 7] * i1));
  stg_publish(c);
}

struct SmState { float m0, m1, l0, l1, k0, k1, a0, a1; };

template<bool SAFE>
__device__ __forceinline__ void softmax_step(float (&S)[64], SmState& z) {
  if (SAFE) {
    float x0 = fmaxf(S[0], S[1]), x1 = fmaxf(S[2], S[3]), y0 = fmaxf(S[4], S[5]), y1 = fmaxf(S[6], S[7]);
    #pragma unroll
    for (int j = 2; j < 16; j += 2) {
      x0 = fmaxf(x0, fmaxf(S[4 * j], S[4 * j + 1]));     x1 = fmaxf(x1, fmaxf(S[4 * j + 2], S[4 * j + 3]));
      y0 = fmaxf(y0, fmaxf(S[4 * j + 4], S[4 * j + 5])); y1 = fmaxf(y1, fmaxf(S[4 * j + 6], S[4 * j + 7]));
    }
    x0 = fmaxf(x0, y0); x1 = fmaxf(x1, y1);
    x0 = fmaxf(x0, __shfl_xor_sync(0xffffffffu, x0, 1)); x1 = fmaxf(x1, __shfl_xor_sync(0xffffffffu, x1, 1));
    x0 = fmaxf(x0, __shfl_xor_sync(0xffffffffu, x0, 2)); x1 = fmaxf(x1, __shfl_xor_sync(0xffffffffu, x1, 2));
    const float n0 = fmaxf(z.m0, x0), n1 = fmaxf(z.m1, x1);
    z.a0 = ex2(z.m0 - n0); z.a1 = ex2(z.m1 - n1);
    z.m0 = n0; z.m1 = n1;
    z.l0 *= z.a0; z.k0 *= z.a0; z.l1 *= z.a1; z.k1 *= z.a1;
  }
  #pragma unroll
  for (int j = 0; j < 16; j++) {
    S[4 * j]     = ex2(SAFE ? S[4 * j] - z.m0     : S[4 * j]);
    S[4 * j + 1] = ex2(SAFE ? S[4 * j + 1] - z.m0 : S[4 * j + 1]);
    S[4 * j + 2] = ex2(SAFE ? S[4 * j + 2] - z.m1 : S[4 * j + 2]);
    S[4 * j + 3] = ex2(SAFE ? S[4 * j + 3] - z.m1 : S[4 * j + 3]);
    z.l0 += S[4 * j]; z.k0 += S[4 * j + 1]; z.l1 += S[4 * j + 2]; z.k1 += S[4 * j + 3];
  }
}

__device__ __forceinline__ void issue_qk(float (&S)[64], const uint32_t (&Q)[32], uint32_t kaddr) {
  const uint32_t dk = desc_lo(kaddr, 16);
  #pragma unroll
  for (int kk = 0; kk < 8; kk++)
    wgmma_rs_n128<0>(S, Q[4 * kk], Q[4 * kk + 1], Q[4 * kk + 2], Q[4 * kk + 3], dk + (kk >> 2) * 1024 + (kk & 3) * 2, kk != 0);
  wg_commit();
}
__device__ __forceinline__ void issue_pv(float (&O)[64], const uint32_t (&P)[32], uint32_t vaddr, int accumulate) {
  const uint32_t dv = desc_lo(vaddr, 16384);
  #pragma unroll
  for (int kk = 0; kk < 8; kk++)
    wgmma_rs_n128<1>(O, P[4 * kk], P[4 * kk + 1], P[4 * kk + 2], P[4 * kk + 3], dv + kk * 128, kk != 0 ? 1 : accumulate);
  wg_commit();
}
__device__ __forceinline__ void pack_p(uint32_t (&P)[32], const float (&S)[64]) {
  #pragma unroll
  for (int i = 0; i < 32; i++) P[i] = pack_bf16(S[2 * i], S[2 * i + 1]);
}

template<bool SAFE, bool NEWHEAD, int SKS, int SVS>
__device__ __forceinline__ void attn_step(float (&S)[64], float (&O)[64], uint32_t (&P)[32], uint32_t (&Q)[32], SmState& z, Ctx& c,
                                          uint32_t phk, uint32_t phv, int accumulate, uint32_t reload) {
  mbar_wait(c.full0 + SKS * 8, phk);
  mbar_wait(c.full0 + SVS * 8, phv);
  ATT_SYNC(c.w);
  reg_define(S);
  wg_fence();
  issue_qk(S, Q, c.base + SKS * STAGE_BYTES + A_BYTES);
  issue_pv(O, P, c.base + SVS * STAGE_BYTES + A_BYTES, accumulate);
  ATT_ARRIVE(c.w);
  wg_wait<1>();
  reg_fence(S);
  c.release(SKS);
  if (reload) {
    #pragma unroll
    for (int v = 0; v < 8; v++)
      asm volatile("ld.shared.v4.b32 {%0, %1, %2, %3}, [%4];" : "=r"(Q[4 * v]), "=r"(Q[4 * v + 1]), "=r"(Q[4 * v + 2]), "=r"(Q[4 * v + 3])
        : "r"(reload + (v >> 2) * 8192 + (v & 3) * 512) : "memory");
  }
  const float lp0 = z.l0 + z.k0, lp1 = z.l1 + z.k1;
  if (NEWHEAD) { z.m0 = -INFINITY; z.m1 = -INFINITY; z.l0 = 0.f; z.l1 = 0.f; z.k0 = 0.f; z.k1 = 0.f; }
  softmax_step<SAFE>(S, z);
  if (z.l0 + z.k0 + z.l1 + z.k1 < 0.f) asm volatile("st.shared.u32 [%0], %1;" :: "r"(c.full0 + 192), "r"(0) : "memory");
  wg_wait<0>();
  reg_fence(O); reg_fence(P);
  c.release(SVS);
  if (SAFE && !NEWHEAD) {
    #pragma unroll
    for (int j = 0; j < 16; j++) { O[4 * j] *= z.a0; O[4 * j + 1] *= z.a0; O[4 * j + 2] *= z.a1; O[4 * j + 3] *= z.a1; }
  }
  pack_p(P, S);
  if (NEWHEAD) o_store(O, lp0, lp1, c);
}

template<bool SAFE>
__device__ __forceinline__ void attention_heads(float (&S)[64], float (&O)[64], uint32_t (&Q)[32], uint32_t stash, Ctx& c, bool last) {
  uint32_t P[32];
  SmState z{-INFINITY, -INFINITY, 0.f, 0.f, 0.f, 0.f, 1.f, 1.f};
  softmax_step<SAFE>(S, z);
  pack_p(P, S);
  #pragma unroll 1
  for (int i = 0; i < 4; i++) {
    const uint32_t ph = i & 1;
    APROF(0);
    attn_step<SAFE, false, 1, 2>(S, O, P, Q, z, c, ph, ph, ph, i == 1 ? stash : 0u);
    APROF(1);
    if (i == 3) break;
    if (i == 1) attn_step<SAFE, true, 3, 0>(S, O, P, Q, z, c, 1, 0, 1, 0u);
    else        attn_step<SAFE, false, 3, 0>(S, O, P, Q, z, c, 0, 1, 1, 0u);
  }
  mbar_wait(c.full0 + 24, 1);
  ATT_SYNC(c.w);
  wg_fence();
  issue_pv(O, P, c.base + 3 * STAGE_BYTES + A_BYTES, 1);
  ATT_ARRIVE(c.w);
  wg_wait<0>();
  reg_fence(O);
  c.release(3);
  o_store(O, z.l0 + z.k0, z.l1 + z.k1, c);
}

constexpr float SM_BOUND = 48.f;

__device__ __forceinline__ void attention_pair(float (&acc)[128], Ctx& c, uint32_t kvbar, bool last) {
  uint32_t Q[32];
  uint32_t n[8] = {0, 0, 0, 0, 0, 0, 0, 0};
  mbar_wait(kvbar, 0);
  stg_acquire(c);
  float qlim;
  asm volatile("ld.shared.f32 %0, [%1];" : "=f"(qlim) : "r"(kvbar + 8) : "memory");
  if (!last) {
    float m0, r0, m1, r1;
    const uint32_t sa = c.base + SMEM_STAT + (c.w * 64 + c.warp * 16 + (c.lane >> 2)) * 8, ca = c.base + SMEM_CS + (c.lane & 3) * 8;
    asm volatile("ld.shared.v2.f32 {%0, %1}, [%2];" : "=f"(m0), "=f"(r0) : "r"(sa) : "memory");
    asm volatile("ld.shared.v2.f32 {%0, %1}, [%2];" : "=f"(m1), "=f"(r1) : "r"(sa + 64) : "memory");
    r0 *= SM_SCALE; r1 *= SM_SCALE; m0 *= -r0; m1 *= -r1;
    #pragma unroll
    for (int i = 0; i < 32; i++) {
      float c0, c1;
      asm volatile("ld.shared.v2.f32 {%0, %1}, [%2];" : "=f"(c0), "=f"(c1) : "r"(ca + i * 32) : "memory");
      acc[4 * i]     = fmaf(acc[4 * i],     r0, m0 * c0); acc[4 * i + 1] = fmaf(acc[4 * i + 1], r0, m0 * c1);
      acc[4 * i + 2] = fmaf(acc[4 * i + 2], r1, m1 * c0); acc[4 * i + 3] = fmaf(acc[4 * i + 3], r1, m1 * c1);
    }
  }
  const uint32_t stash = c.stg + c.warp * 2048 + c.lane * 16;
  #pragma unroll
  for (int v = 0; v < 8; v++) {
    uint32_t r[4];
    #pragma unroll
    for (int e = 0; e < 4; e++) {
      r[e] = pack_bf16(acc[64 + 8 * v + 2 * e], acc[65 + 8 * v + 2 * e]);
      n[4 + e] = bf2_fma(r[e], r[e], n[4 + e]);
      Q[4 * v + e] = pack_bf16(acc[8 * v + 2 * e], acc[8 * v + 2 * e + 1]);
      n[e] = bf2_fma(Q[4 * v + e], Q[4 * v + e], n[e]);
    }
    asm volatile("st.shared.v4.b32 [%0], {%1, %2, %3, %4};" :: "r"(stash + (v >> 2) * 8192 + (v & 3) * 512), "r"(r[0]), "r"(r[1]), "r"(r[2]), "r"(r[3]) : "memory");
  }
  float S[64];
  mbar_wait(c.full0, 0);
  ATT_SYNC(c.w);
  reg_define(S);
  wg_fence();
  issue_qk(S, Q, c.base + A_BYTES);
  ATT_ARRIVE(c.w);
  const uint32_t m0 = bf2_add(n[0], n[2]), m1 = bf2_add(n[1], n[3]), m2 = bf2_add(n[4], n[6]), m3 = bf2_add(n[5], n[7]);
  const bool ok = (bf_lo(m0) + bf_hi(m0) <= qlim) && (bf_lo(m1) + bf_hi(m1) <= qlim) && (bf_lo(m2) + bf_hi(m2) <= qlim) && (bf_lo(m3) + bf_hi(m3) <= qlim);
  uint32_t all_ok;
  asm volatile("{\n.reg .pred p, q;\nsetp.ne.u32 q, %1, 0;\nbarrier.cta.red.and.aligned.pred p, %2, 128, q;\nselp.u32 %0, 1, 0, p;\n}"
    : "=r"(all_ok) : "r"((uint32_t)ok), "r"(3 + c.w) : "memory");
  float O[64];
  #pragma unroll
  for (int i = 0; i < 64; i++) asm volatile("mov.b32 %0, 0;" : "=f"(O[i]));
  wg_wait<0>();
  reg_fence(S);
  c.release(0);
  if (all_ok) attention_heads<false>(S, O, Q, stash, c, last);
  else        attention_heads<true>(S, O, Q, stash, c, last);
}

__device__ __forceinline__ void inbox_load(uint32_t* r, const uint4* p) {
  asm volatile("ld.relaxed.gpu.global.v4.b32 {%0, %1, %2, %3}, [%4];" : "=r"(r[0]), "=r"(r[1]), "=r"(r[2]), "=r"(r[3]) : "l"(p) : "memory");
}
__device__ __forceinline__ void inbox_wait(uint32_t* r, const uint4* p, bool load_first) {
  if (load_first) inbox_load(r, p);
  #pragma unroll 1
  for (int it = 0; it < (1 << 21) && __any_sync(0xffffffffu, min(min(r[0], r[1]), min(r[2], r[3])) == 0); it++) inbox_load(r, p);
}
template<bool TYPE_A>
__device__ __forceinline__ void final_combine(float (&acc)[128], const Ctx& c, const Pipe& p, uint4* outbox, const uint4* inbox,
                                              const CUtensorMap* out_map, int col, int row) {
  constexpr int KEEP = TYPE_A ? 0 : 64, SEND = 64 - KEEP;
  mbar_wait(c.full0 + p.st * 8, p.ph);
  #pragma unroll
  for (int v = 0; v < 8; v++)
    asm volatile("st.relaxed.gpu.global.v4.b32 [%0], {%1, %2, %3, %4};" :: "l"(outbox + v * (16 * S_COLS / 8)),
      "r"(~pack_bf16(acc[SEND + 8 * v], acc[SEND + 8 * v + 1])), "r"(~pack_bf16(acc[SEND + 8 * v + 2], acc[SEND + 8 * v + 3])),
      "r"(~pack_bf16(acc[SEND + 8 * v + 4], acc[SEND + 8 * v + 5])), "r"(~pack_bf16(acc[SEND + 8 * v + 6], acc[SEND + 8 * v + 7])) : "memory");
  PROF(11);
  uint32_t G[32], R[32];
  if (!TYPE_A) {
    #pragma unroll
    for (int i = 0; i < 32; i++) {
      const float y0 = acc[KEEP + 2 * i], y1 = acc[KEEP + 2 * i + 1];
      G[i] = pack_bf16(y0 * rcp(1.0f + ex2(y0 * -1.4426950408889634f)), y1 * rcp(1.0f + ex2(y1 * -1.4426950408889634f)));
    }
    reg_fence(G);
  }
  if (TYPE_A) inbox_wait(R, inbox, true);
  #pragma unroll
  for (int v = TYPE_A ? 1 : 0; v < 8; v++) inbox_load(R + 4 * v, inbox + v * (16 * S_COLS / 8));
  PROF(12);
  #pragma unroll
  for (int b = 0; b < 2; b++) {
    const uint32_t xa = c.base + p.st * STAGE_BYTES + b * 16384 + c.w * 8192;
    #pragma unroll
    for (int q = 0; q < 4; q++) {
      uint32_t xr[4];
      ldsm_x4(xa + c.sw[q], xr[0], xr[1], xr[2], xr[3]);
      inbox_wait(R + b * 16 + q * 4, inbox + (b * 4 + q) * (16 * S_COLS / 8), false);
      #pragma unroll
      for (int e = 0; e < 4; e++) {
        const int i = b * 16 + q * 4 + e;
        uint32_t sv = ~R[i];
        if (TYPE_A) {
          const float y0 = bf_lo(sv), y1 = bf_hi(sv);
          G[i] = pack_bf16(y0 * rcp(1.0f + ex2(y0 * -1.4426950408889634f)), y1 * rcp(1.0f + ex2(y1 * -1.4426950408889634f)));
          sv = pack_bf16(acc[2 * i], acc[2 * i + 1]);
        }
        xr[e] = bf2_add(xr[e], bf2_mul(sv, G[i]));
      }
      stsm_x4(xa + c.sw[q], xr[0], xr[1], xr[2], xr[3]);
    }
    fence_async_smem();
    asm volatile("bar.sync %0, 128;" :: "r"(3 + c.w) : "memory");
    if (c.elect) { tma_store_2d(out_map, xa, col + b * 64, row); bulk_commit(); }
  }
  if (c.elect) bulk_wait_read0();
  PROF(13);
}

__global__ void __cluster_dims__(2, 1, 1) __launch_bounds__(384, 1)
fused_kernel(const __nv_bfloat16* __restrict__ x, const __nv_bfloat16* __restrict__ kc, const __nv_bfloat16* __restrict__ vc,
             const __grid_constant__ Maps maps) {
  extern __shared__ __align__(1024) uint8_t smem_raw[];
  const uint32_t base = smem_u32(smem_raw);
  const uint32_t bars = base + SMEM_BAR;
  const uint32_t full0 = bars, empty0 = bars + 32, sfull0 = bars + 64, sempty0 = bars + 80, kvbar = bars + 96, lnbar = bars + 112,
                 csbar = bars + 128, zbar = bars + 136;
  const int tid = threadIdx.x, lane = tid & 31;
  const int warp_id = __shfl_sync(0xffffffffu, tid >> 5, 0), wg = warp_id >> 2;
  const int rank = blockIdx.x & 1, rb = blockIdx.x & 15, j = blockIdx.x >> 4, jj = j & 3;
  const bool typeA = j < 4;
  const int row0 = rb * 128;
  const int kvrow = (j >> 1) * SK + (SK - WIN);

  if (warp_id != 8) asm volatile("barrier.cluster.arrive.relaxed.aligned;" ::: "memory");
  uint4 xv[2][4], kq, vq;
  if (wg < 2) {
    #pragma unroll
    for (int r = 0; r < 2; r++) {
      const uint4* src = reinterpret_cast<const uint4*>(x + (size_t)(row0 + j * 16 + warp_id * 2 + r) * D_MODEL);
      #pragma unroll
      for (int i = 0; i < 4; i++) xv[r][i] = __ldg(src + i * 32 + lane);
    }
    const size_t off = (size_t)(kvrow + ((j & 1) * 16 + rb) * 16 + warp_id * 2) * 128;
    kq = __ldg(reinterpret_cast<const uint4*>(kc + off) + lane);
    vq = __ldg(reinterpret_cast<const uint4*>(vc + off) + lane);
  }
  if (tid == 256) {
    for (int s = 0; s < NSTAGE; s++) { mbar_init(full0 + s * 8, 1); mbar_init(empty0 + s * 8, 4); }
    for (int s = 0; s < 2; s++) { mbar_init(sfull0 + s * 8, 4); mbar_init(sempty0 + s * 8, 1); }
    mbar_init(kvbar, 1); mbar_init(lnbar, 8); mbar_init(csbar, 1); mbar_init(zbar, 1);
    asm volatile("fence.mbarrier_init.release.cluster;" ::: "memory");
    fence_async_smem();
  }
  if (warp_id == 8) { __syncwarp(); asm volatile("barrier.cluster.arrive.relaxed.aligned;" ::: "memory"); }
  if (wg == 2) asm volatile("barrier.cluster.wait.aligned;" ::: "memory");
  if (tid == 256) {
    #pragma unroll 1
    for (int k = 0; k < NSTAGE; k++) {
      mbar_expect_tx(full0 + k * 8, STAGE_BYTES);
      tma_load_2d(base + k * STAGE_BYTES, &maps.x_ld, full0 + k * 8, k * 64, row0);
      tma_load_3d_mc(base + k * STAGE_BYTES + A_BYTES + rank * 16384, &maps.wq, full0 + k * 8, 0, k * 64 + rank * 32, j * 8);
    }
    mbar_expect_tx(csbar, 32768);
    #pragma unroll 1
    for (int k = 0; k < 4; k++) tma_load_2d(base + SMEM_STG + k * 8192, &maps.wq_cs, csbar, j * 512 + rb * 16, k * 256);
  }

  if (wg == 2) {
    asm volatile("setmaxnreg.dec.sync.aligned.u32 40;");
    unsigned done;
    asm volatile("ld.relaxed.gpu.global.u32 %0, [%1];" : "=r"(done) : "l"(g_flags + F_DONE * 32) : "memory");
    if (warp_id == 8) {
      if (lane == 0) {
        PROF(4);
        Pipe p{0, 0};
        const int nseg = typeA ? 5 : 7;
        #pragma unroll 1
        for (int seg = 0; seg < nseg; seg++) {
          const CUtensorMap* ma = &maps.s_ld; const CUtensorMap* mb;
          int colA = C_XN, k0 = 0, kstep = 256, nk = 16, cg, flag = -1; unsigned cnt = 0; uint32_t bytes = STAGE_BYTES;
          if (seg < 2) {
            mb = &maps.wq; cg = j * 8 + seg * 4;
            if (seg == 0) { ma = &maps.x_ld; colA = 0; } else { colA = C_XQ; flag = F_LN + rb; cnt = 16; }
          } else if (seg < 4) {
            if (typeA) { mb = &maps.w1a; cg = jj * 6 + (seg - 2) * 3; bytes = A_BYTES + 24576; }
            else       { mb = &maps.w1b; cg = 24 + jj * 8 + (seg - 2) * 4; }
          } else {
            cg = jj * 4;
            if (typeA) { mb = &maps.wo; colA = C_O; nk = 64; flag = F_O + rb; cnt = 64; }
            else {
              mb = &maps.w2; colA = C_H;
              if (seg == 4)      { k0 = 1536; kstep = 512; flag = F_HB1 + rb; cnt = 16; }
              else if (seg == 5) { nk = 24; flag = F_HA + rb; cnt = 32; }
              else               { k0 = 1792; kstep = 512; flag = F_HB2 + rb; cnt = 16; }
            }
          }
          PROF(20 + 2 * seg);
          if (flag >= 0) flag_wait(flag, (done / NCTA + 1) * cnt);
          PROF(21 + 2 * seg);
          #pragma unroll 1
          for (int k = seg == 0 ? NSTAGE : 0; k < nk; k++) {
            const int kcol = k0 + (k >> 2) * kstep + (k & 3) * 64;
            const uint32_t sa = base + p.st * STAGE_BYTES, fb = full0 + p.st * 8;
            mbar_wait(empty0 + p.st * 8, p.ph);
            mbar_expect_tx(fb, bytes);
            tma_load_3d_mc(sa + A_BYTES + rank * 16384, mb, fb, 0, kcol + rank * 32, cg);
            tma_load_2d(sa, ma, fb, colA + kcol, row0);
            if (seg == nseg - 1 && k == nk - ZERO_LEAD) mbar_arrive(zbar);
            p.next();
          }
          if (seg < 2) {
            #pragma unroll 1
            for (int i = 0; i < 16; i++) {
              const bool isK = (i == 0) || ((i & 1) && i < 15);
              const int t = isK ? (i + 1) >> 1 : (i - 1) >> 1;
              mbar_wait(empty0 + p.st * 8, p.ph);
              const uint32_t sa = base + p.st * STAGE_BYTES, fb = full0 + p.st * 8;
              mbar_expect_tx(fb, 32768);
              tma_load_2d_mc(sa + A_BYTES + rank * 16384, isK ? &maps.k : &maps.v, fb, rank * 64, kvrow + (t & 3) * 128);
              p.next();
            }
          }
        }
        {
          const uint32_t sa = base + p.st * STAGE_BYTES, fb = full0 + p.st * 8;
          const int col = jj * 256 + (typeA ? 0 : 128);
          flag_wait(F_X + (blockIdx.x ^ 64), done / NCTA + 1);
          mbar_wait(empty0 + p.st * 8, p.ph);
          mbar_expect_tx(fb, 32768);
          tma_load_2d(sa, &maps.x_ld, fb, col, row0);
          tma_load_2d(sa + 16384, &maps.x_ld, fb, col + 64, row0);
        }
        asm volatile("red.relaxed.gpu.global.add.u32 [%0], 1;" :: "l"(g_flags + F_DONE * 32) : "memory");
      }
    } else if (warp_id <= 10) {
      const int w = warp_id - 9;
      {
        mbar_wait(csbar, 0);
        const uint32_t src = base + SMEM_STG + w * 16384 + lane * 16;
        float a[8] = {0.f, 0.f, 0.f, 0.f, 0.f, 0.f, 0.f, 0.f};
        #pragma unroll 4
        for (int r = 0; r < 32; r++) {
          uint32_t v0, v1, v2, v3;
          asm volatile("ld.shared.v4.b32 {%0, %1, %2, %3}, [%4];" : "=r"(v0), "=r"(v1), "=r"(v2), "=r"(v3) : "r"(src + r * 512));
          a[0] += bf_lo(v0); a[1] += bf_hi(v0); a[2] += bf_lo(v1); a[3] += bf_hi(v1);
          a[4] += bf_lo(v2); a[5] += bf_hi(v2); a[6] += bf_lo(v3); a[7] += bf_hi(v3);
        }
        #pragma unroll 1
        for (int o = 2; o < 32; o <<= 1) {
          #pragma unroll
          for (int i = 0; i < 8; i++) a[i] += __shfl_xor_sync(0xffffffffu, a[i], o);
        }
        if (lane < 2) {
          asm volatile("st.shared.v4.f32 [%0], {%1, %2, %3, %4};" :: "r"(base + SMEM_CS + w * 64 + lane * 32), "f"(a[0]), "f"(a[1]), "f"(a[2]), "f"(a[3]) : "memory");
          asm volatile("st.shared.v4.f32 [%0], {%1, %2, %3, %4};" :: "r"(base + SMEM_CS + w * 64 + lane * 32 + 16), "f"(a[4]), "f"(a[5]), "f"(a[6]), "f"(a[7]) : "memory");
        }
        asm volatile("bar.arrive 5, 96;" ::: "memory");
        asm volatile("bar.sync 6, 96;" ::: "memory");
        #pragma unroll 1
        for (int r = w * 8; r < w * 8 + 8; r++) {
          const size_t row = row0 + j * 16 + r;
          const uint4* xs = reinterpret_cast<const uint4*>(x + row * D_MODEL) + lane;
          uint4* dst = reinterpret_cast<uint4*>(g_scratch + row * S_COLS) + lane;
          uint4 v[4];
          #pragma unroll
          for (int i = 0; i < 4; i++) v[i] = __ldg(xs + i * 32);
          float mean, inv;
          asm volatile("ld.shared.v2.f32 {%0, %1}, [%2];" : "=f"(mean), "=f"(inv) : "r"(base + SMEM_OWN + r * 8) : "memory");
          const uint32_t mb = pack_bf16(mean, mean);
          const float invq = inv * SM_SCALE;
          #pragma unroll
          for (int i = 0; i < 4; i++) {
            const uint32_t d0 = bf2_sub(v[i].x, mb), d1 = bf2_sub(v[i].y, mb), d2 = bf2_sub(v[i].z, mb), d3 = bf2_sub(v[i].w, mb);
            dst[C_XN / 8 + i * 32] = make_uint4(pack_bf16(bf_lo(d0) * inv, bf_hi(d0) * inv), pack_bf16(bf_lo(d1) * inv, bf_hi(d1) * inv),
                                                pack_bf16(bf_lo(d2) * inv, bf_hi(d2) * inv), pack_bf16(bf_lo(d3) * inv, bf_hi(d3) * inv));
            dst[C_XQ / 8 + i * 32] = make_uint4(pack_bf16(bf_lo(d0) * invq, bf_hi(d0) * invq), pack_bf16(bf_lo(d1) * invq, bf_hi(d1) * invq),
                                                pack_bf16(bf_lo(d2) * invq, bf_hi(d2) * invq), pack_bf16(bf_lo(d3) * invq, bf_hi(d3) * invq));
          }
        }
        __syncwarp();
      }
      if (lane == 0) {
        flag_signal(F_LN + rb);
        const uint32_t sfull = sfull0 + w * 8, sempty = sempty0 + w * 8, stg = base + SMEM_STG + w * 16384;
        const int row = row0 + w * 64;
        #pragma unroll 1
        for (int job = 0; job < 8; job++) {
          int col, nb = 2, flag;
          if (job < 4) { col = C_O + (j * 4 + job) * 128; flag = F_O + rb; }
          else {
            const int t = (job - 4) >> 1, part = job & 1;
            if (typeA) { col = C_H + jj * 384 + t * 192 + part * 128; nb = 2 - part; flag = F_HA + rb; }
            else       { col = C_H + 1536 + jj * 512 + t * 256 + part * 128; flag = (t == 0 ? F_HB1 : F_HB2) + rb; }
          }
          mbar_wait(sfull, job & 1);
          #pragma unroll 1
          for (int b = 0; b < nb; b++) {
            tma_store_2d(&maps.s_st, stg + b * 8192, col + b * 64, row);
            bulk_commit();
            bulk_wait_read0();
          }
          mbar_arrive(sempty);
          bulk_wait0();
          HPROF(36 + w * 8 + job);
          flag_signal(flag);
        }
      }
    } else {
      const unsigned ep = done / NCTA + 1;
      HPROF(8);
      mbar_wait(lnbar, 0);
      if (lane < 16) {
        float2 st;
        asm volatile("ld.shared.v2.f32 {%0, %1}, [%2];" : "=f"(st.x), "=f"(st.y) : "r"(base + SMEM_OWN + lane * 8) : "memory");
        g_sync.stats[row0 + j * 16 + lane] = st;
      }
      {
        uint32_t m;
        asm volatile("ld.shared.u32 %0, [%1];" : "=r"(m) : "r"(base + SMEM_OWN + 128 + (lane & 15) * 4) : "memory");
        #pragma unroll
        for (int o = 2; o < 16; o <<= 1) m = max(m, __shfl_xor_sync(0xffffffffu, m, o));
        if (lane < 2)
          asm volatile("red.relaxed.gpu.global.max.u64 [%0], %1;" :: "l"(g_sync.kvmax + (j >> 1) * 32 + lane * 16), "l"(((unsigned long long)ep << 32) | m) : "memory");
      }
      asm volatile("bar.sync 5, 96;" ::: "memory");
      HPROF(9);
      if (lane < 16) {
        float u, v;
        asm volatile("ld.shared.f32 %0, [%1];" : "=f"(u) : "r"(base + SMEM_CS + lane * 4) : "memory");
        asm volatile("ld.shared.f32 %0, [%1];" : "=f"(v) : "r"(base + SMEM_CS + 64 + lane * 4) : "memory");
        g_sync.colsum[j * 256 + rb * 16 + lane] = u + v;
      }
      __syncwarp();
      unsigned* const fl = g_flags + (lane == 0 ? F_ST + rb : lane == 1 ? F_CS + j : F_KV + (j >> 1)) * 32;
      if (lane < 3) {
        HPROF(12);
        asm volatile("red.release.gpu.global.add.u32 [%0], 1;" :: "l"(fl) : "memory");
        HPROF(13);
      }
      __syncwarp();
      asm volatile("bar.arrive 6, 96;" ::: "memory");
      if (lane < 3) {
        asm volatile("{\n.reg .pred p;\n.reg .u32 c, v;\nmov.u32 c, 0;\n"
          "WAIT:\n"
          "ld.acquire.gpu.global.u32 v, [%0];\n"
          "sub.u32 v, v, %1;\n"
          "setp.ge.s32 p, v, 0;\n"
          "@p bra DONE;\n"
          "add.u32 c, c, 1;\n"
          "setp.gt.u32 p, c, 0x400000;\n"
          "@p trap;\n"
          "bra WAIT;\n"
          "DONE:\n}" :: "l"(fl), "r"(ep * (8u << lane)) : "memory");
      }
      __syncwarp();
      HPROF(11);
      const float4 s0 = __ldcg(reinterpret_cast<const float4*>(g_sync.stats + row0) + lane), s1 = __ldcg(reinterpret_cast<const float4*>(g_sync.stats + row0) + 32 + lane);
      const float4 c0 = __ldcg(reinterpret_cast<const float4*>(g_sync.colsum + j * 256) + lane), c1 = __ldcg(reinterpret_cast<const float4*>(g_sync.colsum + j * 256) + 32 + lane);
      const float k2 = __uint_as_float((unsigned)__ldcg(g_sync.kvmax + (j >> 1) * 32)), va = __uint_as_float((unsigned)__ldcg(g_sync.kvmax + (j >> 1) * 32 + 16));
      asm volatile("st.shared.v4.f32 [%0], {%1, %2, %3, %4};" :: "r"(base + SMEM_STAT + lane * 16), "f"(s0.x), "f"(s0.y), "f"(s0.z), "f"(s0.w) : "memory");
      asm volatile("st.shared.v4.f32 [%0], {%1, %2, %3, %4};" :: "r"(base + SMEM_STAT + 512 + lane * 16), "f"(s1.x), "f"(s1.y), "f"(s1.z), "f"(s1.w) : "memory");
      asm volatile("st.shared.v4.f32 [%0], {%1, %2, %3, %4};" :: "r"(base + SMEM_CS + lane * 16), "f"(c0.x), "f"(c0.y), "f"(c0.z), "f"(c0.w) : "memory");
      asm volatile("st.shared.v4.f32 [%0], {%1, %2, %3, %4};" :: "r"(base + SMEM_CS + 512 + lane * 16), "f"(c1.x), "f"(c1.y), "f"(c1.z), "f"(c1.w) : "memory");
      __syncwarp();
      if (lane == 0) {
        float qlim = __fdividef(SM_BOUND * SM_BOUND * 0.25f * 0.9f, k2);
        if (!(va >= 0x1p-50f && va <= 0x1p60f) || !(k2 <= 0x1p120f)) qlim = -1.f;
        asm volatile("st.shared.f32 [%0], %1;" :: "r"(kvbar + 8), "f"(qlim) : "memory");
        mbar_arrive(kvbar);
      }
      mbar_wait(zbar, 0);
      #pragma unroll 4
      for (int i = 0; i < 64; i++)
        reinterpret_cast<uint4*>(g_scratch + (size_t)(row0 + i * 2 + (lane >> 4)) * S_COLS + C_X + j * 128)[lane & 15] = make_uint4(0, 0, 0, 0);
      __syncwarp();
      if (lane == 0) flag_signal(F_X + blockIdx.x);
      HPROF(14);
    }
  } else {
    PROF(0);
    {
      float s[2], q[2];
      #pragma unroll
      for (int r = 0; r < 2; r++) {
        const uint32_t* u = reinterpret_cast<const uint32_t*>(xv[r]);
        float a = 0.f, b = 0.f;
        #pragma unroll
        for (int i = 0; i < 16; i++) { a += bf_lo(u[i]); b += bf_hi(u[i]); }
        s[r] = a + b;
      }
      #pragma unroll
      for (int o = 16; o > 0; o >>= 1) { s[0] += __shfl_xor_sync(0xffffffffu, s[0], o); s[1] += __shfl_xor_sync(0xffffffffu, s[1], o); }
      #pragma unroll
      for (int r = 0; r < 2; r++) {
        const uint32_t* u = reinterpret_cast<const uint32_t*>(xv[r]);
        s[r] *= (1.0f / D_MODEL);
        float a = 0.f, b = 0.f;
        #pragma unroll
        for (int i = 0; i < 16; i++) { const float d = bf_lo(u[i]) - s[r], e = bf_hi(u[i]) - s[r]; a = fmaf(d, d, a); b = fmaf(e, e, b); }
        q[r] = a + b;
      }
      #pragma unroll
      for (int o = 16; o > 0; o >>= 1) { q[0] += __shfl_xor_sync(0xffffffffu, q[0], o); q[1] += __shfl_xor_sync(0xffffffffu, q[1], o); }
      const uint32_t ku[4] = {kq.x, kq.y, kq.z, kq.w}, vu[4] = {vq.x, vq.y, vq.z, vq.w};
      float k2 = 0.f; uint32_t vm = 0;
      #pragma unroll
      for (int i = 0; i < 4; i++) {
        k2 = fmaf(bf_lo(ku[i]), bf_lo(ku[i]), k2); k2 = fmaf(bf_hi(ku[i]), bf_hi(ku[i]), k2);
        vm = max(vm, max((vu[i] << 16) & 0x7fffffffu, vu[i] & 0x7fff0000u));
      }
      #pragma unroll
      for (int o = 8; o > 0; o >>= 1) k2 += __shfl_xor_sync(0xffffffffu, k2, o);
      const uint32_t k2m = __reduce_max_sync(0xffffffffu, __float_as_uint(k2) & 0x7fffffffu);
      vm = __reduce_max_sync(0xffffffffu, vm);
      asm volatile("barrier.cluster.wait.aligned;" ::: "memory");
      if (lane == 0) {
        asm volatile("st.shared.v2.u32 [%0], {%1, %2};" :: "r"(base + SMEM_OWN + 128 + warp_id * 8), "r"(k2m), "r"(vm) : "memory");
        #pragma unroll
        for (int r = 0; r < 2; r++) {
          float den;
          asm("sqrt.approx.f32 %0, %1;" : "=f"(den) : "f"(round_bf16(round_bf16(q[r] * (1.0f / D_MODEL)) + 1e-5f)));
          asm volatile("st.shared.v2.f32 [%0], {%1, %2};" :: "r"(base + SMEM_OWN + (warp_id * 2 + r) * 8), "f"(round_bf16(s[r])), "f"(rcp(round_bf16(den))) : "memory");
        }
        mbar_arrive(lnbar);
      }
    }
    PROF(1);
    asm volatile("setmaxnreg.inc.sync.aligned.u32 232;");

    Ctx c;
    c.base = base; c.full0 = full0; c.sfull = sfull0 + wg * 8; c.sempty = sempty0 + wg * 8;
    c.stg = base + SMEM_STG + wg * 16384; c.w = wg; c.lane = lane; c.warp = warp_id & 3;
    #pragma unroll
    for (int q = 0; q < 4; q++)
      c.sw[q] = (c.warp * 16 + ((lane >> 3) & 1) * 8 + (lane & 7)) * 128 + ((((q << 1) + (lane >> 4)) ^ (lane & 7)) << 4);
    c.njob = 0; c.elect = (tid & 127) == 0; c.rel = (tid & 95) == 0;
    asm("mapa.shared::cluster.u32 %0, %1, %2;" : "=r"(c.relbar) : "r"(empty0), "r"((tid >> 5) & 1));
    Pipe p{0, 0};
    if (wg == 1) turn_arrive(1);
    uint4* const xch = reinterpret_cast<uint4*>(g_scratch + (size_t)(row0 + (tid >> 4)) * S_COLS + C_X) + (tid & 15);
    float acc[128];
    uint32_t held[32];
    #pragma unroll 1
    for (int pr = 0; pr < 2; pr++) {
      gemm_tile<256, 0>(acc, held, c, p, 16);
      PROF(2 + 2 * pr);
      attention_pair(acc, c, kvbar, pr == 1);
      PROF(3 + 2 * pr);
    }
    if (typeA) {
      gemm_tile<192, 0>(acc, held, c, p, 16);
      PROF(6);
      epi_relu<3>(acc, held, c);
      PROF(7);
      gemm_tile<192, 1>(acc, held, c, p, 16);
      PROF(8);
      epi_relu<3>(acc, held, c);
      PROF(9);
      gemm_tile<256, 1, true>(acc, held, c, p, 64);
      PROF(10);
      final_combine<true>(acc, c, p, xch + (j ^ 4) * 16, xch + j * 16, &maps.out_st, jj * 256, row0 + wg * 64);
    } else {
      gemm_tile<256, 0>(acc, held, c, p, 16);
      PROF(6);
      epi_relu<4>(acc, held, c);
      PROF(7);
      gemm_tile<256, 2>(acc, held, c, p, 16);
      PROF(8);
      epi_relu<4>(acc, held, c);
      PROF(9);
      gemm_tile<256, 2, true>(acc, held, c, p, 56);
      PROF(10);
      final_combine<false>(acc, c, p, xch + (j ^ 4) * 16, xch + j * 16, &maps.out_st, jj * 256 + 128, row0 + wg * 64);
    }
    if (wg == 0) turn_sync(0);
    PROFG(62); PROF(63);
  }
}

typedef CUresult (*EncodeFn)(CUtensorMap*, CUtensorMapDataType, cuuint32_t, void*, const cuuint64_t*, const cuuint64_t*, const cuuint32_t*,
                             const cuuint32_t*, CUtensorMapInterleave, CUtensorMapSwizzle, CUtensorMapL2promotion, CUtensorMapFloatOOBfill);

void map2d(EncodeFn enc, CUtensorMap* m, const void* p, uint64_t rows, uint64_t cols, uint32_t box_rows) {
  cuuint64_t dims[2] = {cols, rows}; cuuint64_t strides[1] = {cols * 2};
  cuuint32_t box[2] = {64, box_rows}; cuuint32_t es[2] = {1, 1};
  enc(m, CU_TENSOR_MAP_DATA_TYPE_BFLOAT16, 2, const_cast<void*>(p), dims, strides, box, es, CU_TENSOR_MAP_INTERLEAVE_NONE,
      CU_TENSOR_MAP_SWIZZLE_128B, CU_TENSOR_MAP_L2_PROMOTION_L2_256B, CU_TENSOR_MAP_FLOAT_OOB_FILL_NONE);
}
void map3d(EncodeFn enc, CUtensorMap* m, const void* p, uint64_t rows, uint64_t cols, uint32_t box_rows, uint32_t groups) {
  cuuint64_t dims[3] = {64, rows, cols / 64}; cuuint64_t strides[2] = {cols * 2, 128};
  cuuint32_t box[3] = {64, box_rows, groups}; cuuint32_t es[3] = {1, 1, 1};
  enc(m, CU_TENSOR_MAP_DATA_TYPE_BFLOAT16, 3, const_cast<void*>(p), dims, strides, box, es, CU_TENSOR_MAP_INTERLEAVE_NONE,
      CU_TENSOR_MAP_SWIZZLE_128B, CU_TENSOR_MAP_L2_PROMOTION_L2_256B, CU_TENSOR_MAP_FLOAT_OOB_FILL_NONE);
}

void map_cs(EncodeFn enc, CUtensorMap* m, const void* p) {
  cuuint64_t dims[2] = {4096, D_MODEL}; cuuint64_t strides[1] = {4096 * 2};
  cuuint32_t box[2] = {16, 256}; cuuint32_t es[2] = {1, 1};
  enc(m, CU_TENSOR_MAP_DATA_TYPE_BFLOAT16, 2, const_cast<void*>(p), dims, strides, box, es, CU_TENSOR_MAP_INTERLEAVE_NONE,
      CU_TENSOR_MAP_SWIZZLE_NONE, CU_TENSOR_MAP_L2_PROMOTION_L2_128B, CU_TENSOR_MAP_FLOAT_OOB_FILL_NONE);
}

}

extern "C" void kernel_launch(void* const* d_in, const int* in_sizes, int n_in, void* d_out, int out_size) {
  (void)in_sizes; (void)n_in; (void)out_size;
  static EncodeFn enc = nullptr;
  static void* scratch = nullptr;
  if (!enc) {
    void* fn = nullptr; cudaDriverEntryPointQueryResult st;
    cudaGetDriverEntryPoint("cuTensorMapEncodeTiled", &fn, cudaEnableDefault, &st);
    enc = (EncodeFn)fn;
    cudaGetSymbolAddress(&scratch, g_scratch);
    cudaFuncSetAttribute(fused_kernel, cudaFuncAttributeMaxDynamicSharedMemorySize, SMEM_TOTAL);
  }
  Maps m;
  map2d(enc, &m.s_ld, scratch, S_ROWS, S_COLS, 128);
  map2d(enc, &m.s_st, scratch, S_ROWS, S_COLS, 64);
  map3d(enc, &m.wq, d_in[3], D_MODEL, 4096, 32, 4);
  map3d(enc, &m.w1a, d_in[6], D_MODEL, DFF, 32, 3);
  map3d(enc, &m.w1b, d_in[6], D_MODEL, DFF, 32, 4);
  map3d(enc, &m.wo, d_in[4], 4096, D_MODEL, 32, 4);
  map3d(enc, &m.w2, d_in[7], DFF, D_MODEL, 32, 4);
  map2d(enc, &m.k, d_in[1], 4 * SK, 128, 128);
  map2d(enc, &m.v, d_in[2], 4 * SK, 128, 128);
  map2d(enc, &m.x_ld, d_in[0], S_ROWS, D_MODEL, 128);
  map2d(enc, &m.out_st, d_out, S_ROWS, D_MODEL, 64);
  map_cs(enc, &m.wq_cs, d_in[3]);
  fused_kernel<<<NCTA, 384, SMEM_TOTAL>>>((const __nv_bfloat16*)d_in[0], (const __nv_bfloat16*)d_in[1], (const __nv_bfloat16*)d_in[2], m);
}
```

```cpp
#include <cuda_runtime.h>
#include <cuda_bf16.h>
#include <cuda.h>
#include <stdint.h>

#define ATT_TURNS 1
#define ATT_SYNC(w) turn_sync(w)
#define ATT_ARRIVE(w) turn_arrive(w)
#define ZERO_LEAD 14
#define RCP_PAIR 1
#define NG 4
#define MID_TURNS 0
#define PRO_SPLIT 16
#define HELD_K 2
namespace {

constexpr int S_ROWS = 2048, D_MODEL = 1024, DFF = 3584, SK = 2048, WIN = 512;
constexpr int C_XN = 0, C_O = 1024, C_H = 5120, C_XQ = 8704, S_COLS = 9728;
constexpr int NSTAGE = 4, STAGE_BYTES = 49152, A_BYTES = 16384;
constexpr int SMEM_STG = NSTAGE * STAGE_BYTES;
constexpr int SMEM_BAR = SMEM_STG + 32768;
constexpr int SMEM_CS = SMEM_BAR + 256;
constexpr int SMEM_STAT = SMEM_CS + 1024;
constexpr int SMEM_OWN = SMEM_STAT + 1024;
constexpr int SMEM_TOTAL = SMEM_OWN + 128 + 64;
constexpr int NCTA = 128;
constexpr float SM_SCALE = 0.08838834764831845f * 1.4426950408889634f;
constexpr int F_LN = 0, F_O = 16, F_HA = 32, F_HB1 = 48, F_HB2 = 64, F_ST = 80, F_CS = 96, F_KV = 104, F_DONE = 108, F_X = 109, NFLAGS = 109 + NCTA;

__device__ __nv_bfloat16 g_scratch[(size_t)S_ROWS * S_COLS];
struct __align__(1024) SyncArea {
  unsigned flags[NFLAGS * 32];
  float2 stats[S_ROWS];
  float colsum[8 * 256];
  unsigned long long kvmax[4 * 2 * 16];
};
__device__ SyncArea g_sync;
__device__ uint4 g_xch[NCTA * 2048];
#define g_flags g_sync.flags
#define PROF(slot) do {} while (0)
#define PPROF(slot) do {} while (0)
#define HPROF(slot) do {} while (0)
#define APROF(k) do {} while (0)
#define BPROF(k) do {} while (0)
#define PROF_SMEM 0

struct Maps {
  CUtensorMap s_ld, s_st, wq, w1a, w1b, wo, w2, k, v, x_ld, out_st, wq_cs;
};

__device__ __forceinline__ uint32_t tid_now() { uint32_t t; asm volatile("mov.u32 %0, %%tid.x;" : "=r"(t)); return t; }
__device__ __forceinline__ uint32_t smem_u32(const void* p) { return (uint32_t)__cvta_generic_to_shared(p); }
__device__ __forceinline__ void mbar_init(uint32_t bar, uint32_t cnt) { asm volatile("mbarrier.init.shared::cta.b64 [%0], %1;" :: "r"(bar), "r"(cnt)); }
__device__ __forceinline__ void mbar_expect_tx(uint32_t bar, uint32_t bytes) { asm volatile("mbarrier.arrive.expect_tx.shared::cta.b64 _, [%0], %1;" :: "r"(bar), "r"(bytes) : "memory"); }
__device__ __forceinline__ void mbar_arrive(uint32_t bar) { asm volatile("mbarrier.arrive.shared::cta.b64 _, [%0];" :: "r"(bar) : "memory"); }
__device__ __forceinline__ void mbar_wait(uint32_t bar, uint32_t parity) {
  asm volatile("{\n.reg .pred p;\n.reg .u32 c;\n"
    "mbarrier.try_wait.parity.shared::cta.b64 p, [%0], %1;\n"
    "@p bra DONE;\n"
    "mov.u32 c, 0;\n"
    "WAIT:\n"
    "mbarrier.try_wait.parity.shared::cta.b64 p, [%0], %1;\n"
    "@p bra DONE;\n"
    "add.u32 c, c, 1;\n"
    "setp.gt.u32 p, c, 0x80000;\n"
    "@p trap;\n"
    "bra WAIT;\n"
    "DONE:\n}" :: "r"(bar), "r"(parity) : "memory");
}
__device__ __forceinline__ void tma_load_2d(uint32_t dst, const CUtensorMap* m, uint32_t bar, int c0, int c1) {
  asm volatile("cp.async.bulk.tensor.2d.shared::cluster.global.mbarrier::complete_tx::bytes [%0], [%1, {%3, %4}], [%2];"
    :: "r"(dst), "l"(m), "r"(bar), "r"(c0), "r"(c1) : "memory");
}
__device__ __forceinline__ void tma_load_2d_mc(uint32_t dst, const CUtensorMap* m, uint32_t bar, int c0, int c1) {
  asm volatile("cp.async.bulk.tensor.2d.shared::cluster.global.mbarrier::complete_tx::bytes.multicast::cluster [%0], [%1, {%3, %4}], [%2], %5;"
    :: "r"(dst), "l"(m), "r"(bar), "r"(c0), "r"(c1), "h"((uint16_t)3) : "memory");
}
__device__ __forceinline__ void tma_load_3d_mc(uint32_t dst, const CUtensorMap* m, uint32_t bar, int c0, int c1, int c2) {
  asm volatile("cp.async.bulk.tensor.3d.shared::cluster.global.mbarrier::complete_tx::bytes.multicast::cluster [%0], [%1, {%3, %4, %5}], [%2], %6;"
    :: "r"(dst), "l"(m), "r"(bar), "r"(c0), "r"(c1), "r"(c2), "h"((uint16_t)3) : "memory");
}
__device__ __forceinline__ void tma_store_2d(const CUtensorMap* m, uint32_t src, int c0, int c1) {
  asm volatile("cp.async.bulk.tensor.2d.global.shared::cta.bulk_group [%0, {%2, %3}], [%1];"
    :: "l"(m), "r"(src), "r"(c0), "r"(c1) : "memory");
}
__device__ __forceinline__ void bulk_commit() { asm volatile("cp.async.bulk.commit_group;" ::: "memory"); }
__device__ __forceinline__ void bulk_wait_read0() { asm volatile("cp.async.bulk.wait_group.read 0;" ::: "memory"); }
__device__ __forceinline__ void bulk_wait0() { asm volatile("cp.async.bulk.wait_group 0;" ::: "memory"); }
__device__ __forceinline__ void fence_async_smem() { asm volatile("fence.proxy.async.shared::cta;" ::: "memory"); }
__device__ __forceinline__ void wg_fence() { asm volatile("wgmma.fence.sync.aligned;" ::: "memory"); }
__device__ __forceinline__ void wg_commit() { asm volatile("wgmma.commit_group.sync.aligned;" ::: "memory"); }
template<int N> __device__ __forceinline__ void wg_wait() { asm volatile("wgmma.wait_group.sync.aligned %0;" :: "n"(N) : "memory"); }
__device__ __forceinline__ uint32_t desc_lo(uint32_t addr, uint32_t lbo) { return ((addr & 0x3FFFF) >> 4) | ((lbo >> 4) << 16); }
template<int N, int CNT = N> __device__ __forceinline__ void reg_fence(float (&d)[N]) {
  #pragma unroll
  for (int i = 0; i < CNT; i++) asm volatile("" : "+f"(d[i]) :: "memory");
}
template<int N> __device__ __forceinline__ void reg_fence(uint32_t (&d)[N]) {
  #pragma unroll
  for (int i = 0; i < N; i++) asm volatile("" : "+r"(d[i]) :: "memory");
}
template<int N> __device__ __forceinline__ void reg_define(float (&d)[N]) {
  #pragma unroll
  for (int i = 0; i < N; i++) asm volatile("" : "=f"(d[i]));
}
__device__ __forceinline__ void flag_signal(int f) { asm volatile("red.release.gpu.global.add.u32 [%0], 1;" :: "l"(g_flags + f * 32) : "memory"); }
__device__ __forceinline__ void flag_wait(int f, unsigned target) {
  asm volatile("{\n.reg .pred p;\n.reg .u32 c, v;\nmov.u32 c, 0;\n"
    "WAIT:\n"
    "ld.acquire.gpu.global.u32 v, [%0];\n"
    "sub.u32 v, v, %1;\n"
    "setp.ge.s32 p, v, 0;\n"
    "@p bra DONE;\n"
    "add.u32 c, c, 1;\n"
    "setp.gt.u32 p, c, 0x400000;\n"
    "@p trap;\n"
    "bra WAIT;\n"
    "DONE:\n"
    "fence.proxy.async.global;\n}" :: "l"(g_flags + f * 32), "r"(target) : "memory");
}
__device__ __forceinline__ uint32_t pack_bf16(float lo, float hi) { uint32_t r; asm("cvt.rn.bf16x2.f32 %0, %1, %2;" : "=r"(r) : "f"(hi), "f"(lo)); return r; }
__device__ __forceinline__ uint32_t pack_bf16_relu(float lo, float hi) { uint32_t r; asm("cvt.rn.relu.bf16x2.f32 %0, %1, %2;" : "=r"(r) : "f"(hi), "f"(lo)); return r; }
__device__ __forceinline__ float bf_lo(uint32_t v) { return __uint_as_float(v << 16); }
__device__ __forceinline__ float bf_hi(uint32_t v) { return __uint_as_float(v & 0xffff0000u); }
__device__ __forceinline__ float round_bf16(float x) { return bf_lo(pack_bf16(x, x)); }
__device__ __forceinline__ uint32_t bf2_sub(uint32_t a, uint32_t b) { uint32_t r; asm("sub.rn.bf16x2 %0, %1, %2;" : "=r"(r) : "r"(a), "r"(b)); return r; }
__device__ __forceinline__ uint32_t bf2_add(uint32_t a, uint32_t b) { uint32_t r; asm("add.rn.bf16x2 %0, %1, %2;" : "=r"(r) : "r"(a), "r"(b)); return r; }
__device__ __forceinline__ uint32_t bf2_mul(uint32_t a, uint32_t b) { uint32_t r; asm("mul.rn.bf16x2 %0, %1, %2;" : "=r"(r) : "r"(a), "r"(b)); return r; }
__device__ __forceinline__ uint32_t bf2_fma(uint32_t a, uint32_t b, uint32_t c) { uint32_t r; asm("fma.rn.bf16x2 %0, %1, %2, %3;" : "=r"(r) : "r"(a), "r"(b), "r"(c)); return r; }
__device__ __forceinline__ float ex2(float x) { float r; asm("ex2.approx.ftz.f32 %0, %1;" : "=f"(r) : "f"(x)); return r; }
__device__ __forceinline__ float rcp(float x) { float r; asm("rcp.approx.ftz.f32 %0, %1;" : "=f"(r) : "f"(x)); return r; }
__device__ __forceinline__ void stsm_x4(uint32_t addr, uint32_t r0, uint32_t r1, uint32_t r2, uint32_t r3) {
  asm volatile("stmatrix.sync.aligned.m8n8.x4.shared.b16 [%0], {%1, %2, %3, %4};" :: "r"(addr), "r"(r0), "r"(r1), "r"(r2), "r"(r3) : "memory");
}
__device__ __forceinline__ void ldsm_x4(uint32_t addr, uint32_t& r0, uint32_t& r1, uint32_t& r2, uint32_t& r3) {
  asm volatile("ldmatrix.sync.aligned.m8n8.x4.shared.b16 {%0, %1, %2, %3}, [%4];" : "=r"(r0), "=r"(r1), "=r"(r2), "=r"(r3) : "r"(addr) : "memory");
}

template<int TB> __device__ __forceinline__ void wgmma_ss_n256(float (&d)[128], uint32_t descA, uint32_t descB, int scaleD) {
  asm volatile("{\n.reg .pred p;\n.reg .b64 da, db;\nmov.b64 da, {%128, 0x40000040};\nmov.b64 db, {%129, 0x40000040};\nsetp.ne.b32 p, %130, 0;\n"
    "wgmma.mma_async.sync.aligned.m64n256k16.f32.bf16.bf16 {"
    "%0, %1, %2, %3, %4, %5, %6, %7, %8, %9, %10, %11, %12, %13, %14, %15, "
    "%16, %17, %18, %19, %20, %21, %22, %23, %24, %25, %26, %27, %28, %29, %30, %31, "
    "%32, %33, %34, %35, %36, %37, %38, %39, %40, %41, %42, %43, %44, %45, %46, %47, "
    "%48, %49, %50, %51, %52, %53, %54, %55, %56, %57, %58, %59, %60, %61, %62, %63, "
    "%64, %65, %66, %67, %68, %69, %70, %71, %72, %73, %74, %75, %76, %77, %78, %79, "
    "%80, %81, %82, %83, %84, %85, %86, %87, %88, %89, %90, %91, %92, %93, %94, %95, "
    "%96, %97, %98, %99, %100, %101, %102, %103, %104, %105, %106, %107, %108, %109, %110, %111, "
    "%112, %113, %114, %115, %116, %117, %118, %119, %120, %121, %122, %123, %124, %125, %126, %127"
    "}, da, db, p, 1, 1, 0, %131;\n}\n"
    : "+f"(d[0]), "+f"(d[1]), "+f"(d[2]), "+f"(d[3]), "+f"(d[4]), "+f"(d[5]), "+f"(d[6]), "+f"(d[7]), "+f"(d[8]), "+f"(d[9]), "+f"(d[10]),
      "+f"(d[11]), "+f"(d[12]), "+f"(d[13]), "+f"(d[14]), "+f"(d[15]), "+f"(d[16]), "+f"(d[17]), "+f"(d[18]), "+f"(d[19]), "+f"(d[20]), "+f"(d[21]),
      "+f"(d[22]), "+f"(d[23]), "+f"(d[24]), "+f"(d[25]), "+f"(d[26]), "+f"(d[27]), "+f"(d[28]), "+f"(d[29]), "+f"(d[30]), "+f"(d[31]), "+f"(d[32]),
      "+f"(d[33]), "+f"(d[34]), "+f"(d[35]), "+f"(d[36]), "+f"(d[37]), "+f"(d[38]), "+f"(d[39]), "+f"(d[40]), "+f"(d[41]), "+f"(d[42]), "+f"(d[43]),
      "+f"(d[44]), "+f"(d[45]), "+f"(d[46]), "+f"(d[47]), "+f"(d[48]), "+f"(d[49]), "+f"(d[50]), "+f"(d[51]), "+f"(d[52]), "+f"(d[53]), "+f"(d[54]),
      "+f"(d[55]), "+f"(d[56]), "+f"(d[57]), "+f"(d[58]), "+f"(d[59]), "+f"(d[60]), "+f"(d[61]), "+f"(d[62]), "+f"(d[63]), "+f"(d[64]), "+f"(d[65]),
      "+f"(d[66]), "+f"(d[67]), "+f"(d[68]), "+f"(d[69]), "+f"(d[70]), "+f"(d[71]), "+f"(d[72]), "+f"(d[73]), "+f"(d[74]), "+f"(d[75]), "+f"(d[76]),
      "+f"(d[77]), "+f"(d[78]), "+f"(d[79]), "+f"(d[80]), "+f"(d[81]), "+f"(d[82]), "+f"(d[83]), "+f"(d[84]), "+f"(d[85]), "+f"(d[86]), "+f"(d[87]),
      "+f"(d[88]), "+f"(d[89]), "+f"(d[90]), "+f"(d[91]), "+f"(d[92]), "+f"(d[93]), "+f"(d[94]), "+f"(d[95]), "+f"(d[96]), "+f"(d[97]), "+f"(d[98]),
      "+f"(d[99]), "+f"(d[100]), "+f"(d[101]), "+f"(d[102]), "+f"(d[103]), "+f"(d[104]), "+f"(d[105]), "+f"(d[106]), "+f"(d[107]), "+f"(d[108]),
      "+f"(d[109]), "+f"(d[110]), "+f"(d[111]), "+f"(d[112]), "+f"(d[113]), "+f"(d[114]), "+f"(d[115]), "+f"(d[116]), "+f"(d[117]), "+f"(d[118]),
      "+f"(d[119]), "+f"(d[120]), "+f"(d[121]), "+f"(d[122]), "+f"(d[123]), "+f"(d[124]), "+f"(d[125]), "+f"(d[126]), "+f"(d[127])
    : "r"(descA), "r"(descB), "r"(scaleD), "n"(TB));
}
template<int TB> __device__ __forceinline__ void wgmma_ss_n192(float (&d)[128], uint32_t descA, uint32_t descB, int scaleD) {
  asm volatile("{\n.reg .pred p;\n.reg .b64 da, db;\nmov.b64 da, {%96, 0x40000040};\nmov.b64 db, {%97, 0x40000040};\nsetp.ne.b32 p, %98, 0;\n"
    "wgmma.mma_async.sync.aligned.m64n192k16.f32.bf16.bf16 {"
    "%0, %1, %2, %3, %4, %5, %6, %7, %8, %9, %10, %11, %12, %13, %14, %15, "
    "%16, %17, %18, %19, %20, %21, %22, %23, %24, %25, %26, %27, %28, %29, %30, %31, "
    "%32, %33, %34, %35, %36, %37, %38, %39, %40, %41, %42, %43, %44, %45, %46, %47, "
    "%48, %49, %50, %51, %52, %53, %54, %55, %56, %57, %58, %59, %60, %61, %62, %63, "
    "%64, %65, %66, %67, %68, %69, %70, %71, %72, %73, %74, %75, %76, %77, %78, %79, "
    "%80, %81, %82, %83, %84, %85, %86, %87, %88, %89, %90, %91, %92, %93, %94, %95"
    "}, da, db, p, 1, 1, 0, %99;\n}\n"
    : "+f"(d[0]), "+f"(d[1]), "+f"(d[2]), "+f"(d[3]), "+f"(d[4]), "+f"(d[5]), "+f"(d[6]), "+f"(d[7]), "+f"(d[8]), "+f"(d[9]), "+f"(d[10]),
      "+f"(d[11]), "+f"(d[12]), "+f"(d[13]), "+f"(d[14]), "+f"(d[15]), "+f"(d[16]), "+f"(d[17]), "+f"(d[18]), "+f"(d[19]), "+f"(d[20]), "+f"(d[21]),
      "+f"(d[22]), "+f"(d[23]), "+f"(d[24]), "+f"(d[25]), "+f"(d[26]), "+f"(d[27]), "+f"(d[28]), "+f"(d[29]), "+f"(d[30]), "+f"(d[31]), "+f"(d[32]),
      "+f"(d[33]), "+f"(d[34]), "+f"(d[35]), "+f"(d[36]), "+f"(d[37]), "+f"(d[38]), "+f"(d[39]), "+f"(d[40]), "+f"(d[41]), "+f"(d[42]), "+f"(d[43]),
      "+f"(d[44]), "+f"(d[45]), "+f"(d[46]), "+f"(d[47]), "+f"(d[48]), "+f"(d[49]), "+f"(d[50]), "+f"(d[51]), "+f"(d[52]), "+f"(d[53]), "+f"(d[54]),
      "+f"(d[55]), "+f"(d[56]), "+f"(d[57]), "+f"(d[58]), "+f"(d[59]), "+f"(d[60]), "+f"(d[61]), "+f"(d[62]), "+f"(d[63]), "+f"(d[64]), "+f"(d[65]),
      "+f"(d[66]), "+f"(d[67]), "+f"(d[68]), "+f"(d[69]), "+f"(d[70]), "+f"(d[71]), "+f"(d[72]), "+f"(d[73]), "+f"(d[74]), "+f"(d[75]), "+f"(d[76]),
      "+f"(d[77]), "+f"(d[78]), "+f"(d[79]), "+f"(d[80]), "+f"(d[81]), "+f"(d[82]), "+f"(d[83]), "+f"(d[84]), "+f"(d[85]), "+f"(d[86]), "+f"(d[87]),
      "+f"(d[88]), "+f"(d[89]), "+f"(d[90]), "+f"(d[91]), "+f"(d[92]), "+f"(d[93]), "+f"(d[94]), "+f"(d[95])
    : "r"(descA), "r"(descB), "r"(scaleD), "n"(TB));
}
template<int TB> __device__ __forceinline__ void wgmma_rs_n128(float (&d)[64], uint32_t a0, uint32_t a1, uint32_t a2, uint32_t a3, uint32_t descB, int scaleD) {
  asm volatile("{\n.reg .pred p;\n.reg .b64 db;\nmov.b64 db, {%68, 0x40000040};\nsetp.ne.b32 p, %69, 0;\n"
    "wgmma.mma_async.sync.aligned.m64n128k16.f32.bf16.bf16 {"
    "%0, %1, %2, %3, %4, %5, %6, %7, %8, %9, %10, %11, %12, %13, %14, %15, "
    "%16, %17, %18, %19, %20, %21, %22, %23, %24, %25, %26, %27, %28, %29, %30, %31, "
    "%32, %33, %34, %35, %36, %37, %38, %39, %40, %41, %42, %43, %44, %45, %46, %47, "
    "%48, %49, %50, %51, %52, %53, %54, %55, %56, %57, %58, %59, %60, %61, %62, %63"
    "}, {%64, %65, %66, %67}, db, p, 1, 1, %70;\n}\n"
    : "+f"(d[0]), "+f"(d[1]), "+f"(d[2]), "+f"(d[3]), "+f"(d[4]), "+f"(d[5]), "+f"(d[6]), "+f"(d[7]), "+f"(d[8]), "+f"(d[9]), "+f"(d[10]),
      "+f"(d[11]), "+f"(d[12]), "+f"(d[13]), "+f"(d[14]), "+f"(d[15]), "+f"(d[16]), "+f"(d[17]), "+f"(d[18]), "+f"(d[19]), "+f"(d[20]), "+f"(d[21]),
      "+f"(d[22]), "+f"(d[23]), "+f"(d[24]), "+f"(d[25]), "+f"(d[26]), "+f"(d[27]), "+f"(d[28]), "+f"(d[29]), "+f"(d[30]), "+f"(d[31]), "+f"(d[32]),
      "+f"(d[33]), "+f"(d[34]), "+f"(d[35]), "+f"(d[36]), "+f"(d[37]), "+f"(d[38]), "+f"(d[39]), "+f"(d[40]), "+f"(d[41]), "+f"(d[42]), "+f"(d[43]),
      "+f"(d[44]), "+f"(d[45]), "+f"(d[46]), "+f"(d[47]), "+f"(d[48]), "+f"(d[49]), "+f"(d[50]), "+f"(d[51]), "+f"(d[52]), "+f"(d[53]), "+f"(d[54]),
      "+f"(d[55]), "+f"(d[56]), "+f"(d[57]), "+f"(d[58]), "+f"(d[59]), "+f"(d[60]), "+f"(d[61]), "+f"(d[62]), "+f"(d[63])
    : "r"(a0), "r"(a1), "r"(a2), "r"(a3), "r"(descB), "r"(scaleD), "n"(TB));
}

__device__ __forceinline__ uint32_t box_offset(uint32_t t) {
  return (((t >> 5) & 3) * 16 + ((t >> 3) & 1) * 8 + (t & 7)) * 128 + ((((t >> 4) & 1) ^ (t & 7)) << 4);
}

struct Pipe {
  int st; uint32_t ph;
  __device__ __forceinline__ void next() { if (++st == NSTAGE) { st = 0; ph ^= 1; } }
};

struct Ctx {
  uint32_t base;
  uint32_t full0, sfull, sempty;
  uint32_t stg;
  uint32_t stgw;
  int w;
  int njob;
  bool rel;
  uint32_t relbar;
  __device__ __forceinline__ void release(int st) const {
    if (rel) asm volatile("mbarrier.arrive.shared::cluster.b64 _, [%0];" :: "r"(relbar + st * 8) : "memory");
  }
};

__device__ __forceinline__ void turn_sync(int w) { asm volatile("bar.sync %0, 256;" :: "r"(1 + w) : "memory"); }
__device__ __forceinline__ void turn_arrive(int w) { asm volatile("bar.arrive %0, 256;" :: "r"(2 - w) : "memory"); }

__device__ __forceinline__ void stg_acquire(const Ctx& c) { mbar_wait(c.sempty, (c.njob & 1) ^ 1); }
__device__ __forceinline__ void stg_publish(Ctx& c) {
  fence_async_smem();
  __syncwarp();
  if ((tid_now() & 31) == 0) mbar_arrive(c.sfull);
  c.njob++;
}
__device__ __forceinline__ void stg_store(const uint32_t (&r)[32], Ctx& c) {
  stg_acquire(c);
  #pragma unroll
  for (int q = 0; q < 8; q++) stsm_x4((c.stgw ^ ((q & 3) << 5)) + (q >> 2) * 8192, r[4 * q], r[4 * q + 1], r[4 * q + 2], r[4 * q + 3]);
  stg_publish(c);
}

template<int N, bool FIRST>
__device__ __forceinline__ void gemm_kblock(float (&acc)[128], const Ctx& c, const Pipe& p, bool take, bool give) {
  mbar_wait(c.full0 + p.st * 8, p.ph);
  const uint32_t sa = c.base + p.st * STAGE_BYTES;
  const uint32_t da = desc_lo(sa + c.w * 8192, 16), db = desc_lo(sa + A_BYTES, 4096);
  if (take) turn_sync(c.w);
  wg_fence();
  #pragma unroll
  for (int kk = 0; kk < 4; kk++) {
    if (N == 256) wgmma_ss_n256<1>(acc, da + kk * 2, db + (kk >> 1) * 1024 + (kk & 1) * 128, !(FIRST && kk == 0));
    else          wgmma_ss_n192<1>(acc, da + kk * 2, db + (kk >> 1) * 1024 + (kk & 1) * 128, !(FIRST && kk == 0));
  }
  wg_commit();
  if (give) turn_arrive(c.w);
}
template<int N, bool HELD>
__device__ __forceinline__ void gemm_tile(float (&acc)[128], const uint32_t (&held)[32], Ctx& c, Pipe& p, int nk, bool has_held, bool last) {
  reg_define(acc);
  gemm_kblock<N, true>(acc, c, p, true, true);
  int prev = p.st;
  p.next();
  const int nrel = last ? nk - NSTAGE + 1 : nk, kheld = has_held ? HELD_K : -1;
  #pragma unroll 1
  for (int k = 1; k < nk; k++) {
    gemm_kblock<N, false>(acc, c, p, k == nk - 2, k == nk - 1);
    if (HELD && k == kheld) stg_store(held, c);
    wg_wait<1>();
    if (k <= nrel) c.release(prev);
    prev = p.st;
    p.next();
  }
  wg_wait<0>();
  if (!last) c.release(prev);
  reg_fence<128, N / 2>(acc);
}

template<int NHELD>
__device__ __forceinline__ void epi_relu(float (&acc)[128], uint32_t (&held)[32], Ctx& c) {
  uint32_t r[32];
  #pragma unroll
  for (int i = 0; i < 32; i++) r[i] = pack_bf16_relu(acc[2 * i], acc[2 * i + 1]);
  stg_store(r, c);
  #pragma unroll
  for (int i = 0; i < 32; i++) held[i] = i < NHELD ? pack_bf16_relu(acc[64 + 2 * i], acc[65 + 2 * i]) : 0u;
  reg_fence(held);
}

__device__ __forceinline__ void o_write(const float (&O)[64], float i0, float i1, const Ctx& c) {
  #pragma unroll
  for (int q = 0; q < 8; q++)
    stsm_x4((c.stgw ^ ((q & 3) << 5)) + (q >> 2) * 8192, pack_bf16(O[8 * q] * i0, O[8 * q + 1] * i0), pack_bf16(O[8 * q + 2] * i1, O[8 * q + 3] * i1),
            pack_bf16(O[8 * q + 4] * i0, O[8 * q + 5] * i0), pack_bf16(O[8 * q + 6] * i1, O[8 * q + 7] * i1));
}

struct SmState { float m0, m1, l0, l1, k0, k1, a0, a1; };

template<bool SAFE>
__device__ __forceinline__ void softmax_max(const float (&S)[64], SmState& z) {
  if (SAFE) {
    float x0 = fmaxf(S[0], S[1]), x1 = fmaxf(S[2], S[3]), y0 = fmaxf(S[4], S[5]), y1 = fmaxf(S[6], S[7]);
    #pragma unroll
    for (int j = 2; j < 16; j += 2) {
      x0 = fmaxf(x0, fmaxf(S[4 * j], S[4 * j + 1]));     x1 = fmaxf(x1, fmaxf(S[4 * j + 2], S[4 * j + 3]));
      y0 = fmaxf(y0, fmaxf(S[4 * j + 4], S[4 * j + 5])); y1 = fmaxf(y1, fmaxf(S[4 * j + 6], S[4 * j + 7]));
    }
    x0 = fmaxf(x0, y0); x1 = fmaxf(x1, y1);
    x0 = fmaxf(x0, __shfl_xor_sync(0xffffffffu, x0, 1)); x1 = fmaxf(x1, __shfl_xor_sync(0xffffffffu, x1, 1));
    x0 = fmaxf(x0, __shfl_xor_sync(0xffffffffu, x0, 2)); x1 = fmaxf(x1, __shfl_xor_sync(0xffffffffu, x1, 2));
    const float n0 = fmaxf(z.m0, x0), n1 = fmaxf(z.m1, x1);
    z.a0 = ex2(z.m0 - n0); z.a1 = ex2(z.m1 - n1);
    z.m0 = n0; z.m1 = n1;
    z.l0 *= z.a0; z.k0 *= z.a0; z.l1 *= z.a1; z.k1 *= z.a1;
  }
}
template<bool SAFE, int J0, int J1>
__device__ __forceinline__ void softmax_exp(float (&S)[64], SmState& z) {
  #pragma unroll
  for (int j = J0; j < J1; j++) {
    S[4 * j]     = ex2(SAFE ? S[4 * j] - z.m0     : S[4 * j]);
    S[4 * j + 1] = ex2(SAFE ? S[4 * j + 1] - z.m0 : S[4 * j + 1]);
    S[4 * j + 2] = ex2(SAFE ? S[4 * j + 2] - z.m1 : S[4 * j + 2]);
    S[4 * j + 3] = ex2(SAFE ? S[4 * j + 3] - z.m1 : S[4 * j + 3]);
    z.l0 += S[4 * j]; z.k0 += S[4 * j + 1]; z.l1 += S[4 * j + 2]; z.k1 += S[4 * j + 3];
  }
}

__device__ __forceinline__ void issue_qk(float (&S)[64], const uint32_t (&Q)[32], uint32_t kaddr) {
  const uint32_t dk = desc_lo(kaddr, 16);
  #pragma unroll
  for (int kk = 0; kk < 8; kk++)
    wgmma_rs_n128<0>(S, Q[4 * kk], Q[4 * kk + 1], Q[4 * kk + 2], Q[4 * kk + 3], dk + (kk >> 2) * 1024 + (kk & 3) * 2, kk != 0);
  wg_commit();
}
template<bool RUNTIME>
__device__ __forceinline__ void issue_pv(float (&O)[64], const uint32_t (&P)[32], uint32_t vaddr, int accumulate) {
  const uint32_t dv = desc_lo(vaddr, 16384);
  #pragma unroll
  for (int kk = 0; kk < 8; kk++)
    wgmma_rs_n128<1>(O, P[4 * kk], P[4 * kk + 1], P[4 * kk + 2], P[4 * kk + 3], dv + kk * 128, kk != 0 ? 1 : (RUNTIME ? accumulate : 0));
  wg_commit();
}
__device__ __forceinline__ void pack_p(uint32_t (&P)[32], const float (&S)[64]) {
  #pragma unroll
  for (int i = 0; i < 32; i++) asm volatile("cvt.rn.bf16x2.f32 %0, %1, %2;" : "+r"(P[i]) : "f"(S[2 * i + 1]), "f"(S[2 * i]));
}

__device__ __forceinline__ uint32_t stash_addr(const Ctx& c) { const uint32_t t = tid_now(); return c.stg + ((t >> 5) & 3) * 2048 + (t & 31) * 16; }

__device__ __forceinline__ void row_inverse(const SmState& z, float& i0, float& i1) {
  i0 = z.l0 + z.k0; i1 = z.l1 + z.k1;
  i0 += __shfl_xor_sync(0xffffffffu, i0, 1); i1 += __shfl_xor_sync(0xffffffffu, i1, 1);
  i0 += __shfl_xor_sync(0xffffffffu, i0, 2); i1 += __shfl_xor_sync(0xffffffffu, i1, 2);
  i0 = rcp(i0); i1 = rcp(i1);
}
__device__ __forceinline__ void reload_q(uint32_t (&Q)[32], const Ctx& c, bool doit) {
  const uint32_t stash = stash_addr(c);
  #pragma unroll
  for (int v = 0; v < 8; v++)
    asm volatile("{\n.reg .pred p;\nsetp.ne.u32 p, %5, 0;\n@p ld.shared.v4.b32 {%0, %1, %2, %3}, [%4];\n}"
      : "+r"(Q[4 * v]), "+r"(Q[4 * v + 1]), "+r"(Q[4 * v + 2]), "+r"(Q[4 * v + 3]) : "r"(stash + (v >> 2) * 8192 + (v & 3) * 512), "r"((uint32_t)doit) : "memory");
}

template<bool NEWHEAD, int SKS, int SVS>
__device__ __forceinline__ void fast_step(float (&S)[64], float (&O)[64], uint32_t (&P)[32], uint32_t (&Q)[32], SmState& z, Ctx& c,
                                          uint32_t phk, uint32_t phv, int accumulate, bool reload) {
  mbar_wait(c.full0 + SKS * 8, phk);
  mbar_wait(c.full0 + SVS * 8, phv);
  ATT_SYNC(c.w);
  reg_define(S);
  wg_fence();
  issue_qk(S, Q, c.base + SKS * STAGE_BYTES + A_BYTES);
  issue_pv<true>(O, P, c.base + SVS * STAGE_BYTES + A_BYTES, accumulate);
  ATT_ARRIVE(c.w);
  float i0, i1;
  if (NEWHEAD) {
    row_inverse(z, i0, i1);
    z.l0 = 0.f; z.l1 = 0.f; z.k0 = 0.f; z.k1 = 0.f;
    stg_acquire(c);
  }
  wg_wait<1>();
  reg_fence(S);
  c.release(SKS);
  if (SKS == 1) reload_q(Q, c, reload);
  softmax_exp<false, 0, 16>(S, z);
  if (z.l0 + z.k0 + z.l1 + z.k1 < 0.f) asm volatile("st.shared.u32 [%0], %1;" :: "r"(c.full0 + 192), "r"(0) : "memory");
  wg_wait<0>();
  reg_fence(O); reg_fence(P);
  c.release(SVS);
  if (NEWHEAD) o_write(O, i0, i1, c);
  pack_p(P, S);
  if (NEWHEAD) stg_publish(c);
}

template<bool SAFE>
__device__ __forceinline__ void exp_pack(const float (&S)[64], uint32_t (&P)[32], SmState& z) {
  #pragma unroll
  for (int j = 0; j < 16; j++) {
    const float e0 = ex2(SAFE ? S[4 * j] - z.m0 : S[4 * j]),         e1 = ex2(SAFE ? S[4 * j + 1] - z.m0 : S[4 * j + 1]);
    const float e2 = ex2(SAFE ? S[4 * j + 2] - z.m1 : S[4 * j + 2]), e3 = ex2(SAFE ? S[4 * j + 3] - z.m1 : S[4 * j + 3]);
    z.l0 += e0; z.k0 += e1; z.l1 += e2; z.k1 += e3;
    P[2 * j] = pack_bf16(e0, e1); P[2 * j + 1] = pack_bf16(e2, e3);
  }
}
__device__ __forceinline__ void first_qk(float (&S)[64], float (&O)[64], const uint32_t (&Q)[32], Ctx& c) {
  mbar_wait(c.full0, 0);
  mbar_wait(c.full0 + 8, 0);
  ATT_SYNC(c.w);
  reg_define(O); reg_define(S);
  wg_fence();
  issue_qk(O, Q, c.base + A_BYTES);
  issue_qk(S, Q, c.base + STAGE_BYTES + A_BYTES);
  ATT_ARRIVE(c.w);
}
__device__ __forceinline__ void first_pv(float (&O)[64], const uint32_t (&P)[32], Ctx& c) {
  mbar_wait(c.full0 + 16, 0);
  ATT_SYNC(c.w);
  wg_fence();
  issue_pv<false>(O, P, c.base + 2 * STAGE_BYTES + A_BYTES, 0);
  ATT_ARRIVE(c.w);
}

__device__ __forceinline__ void fast_heads(float (&S)[64], float (&O)[64], uint32_t (&P)[32], uint32_t (&Q)[32], SmState& z, Ctx& c, bool last) {
  first_qk(S, O, Q, c);
  BPROF(32);
  wg_wait<1>();
  reg_fence(O);
  BPROF(34);
  c.release(0);
  exp_pack<false>(O, P, z);
  reg_fence(P);
  first_pv(O, P, c);
  wg_wait<1>();
  reg_fence(S);
  c.release(1);
  softmax_exp<false, 0, PRO_SPLIT>(S, z);
  if (PRO_SPLIT > 0 && z.l0 + z.k0 + z.l1 + z.k1 < 0.f) asm volatile("st.shared.u32 [%0], %1;" :: "r"(c.full0 + 192), "r"(0) : "memory");
  wg_wait<0>();
  reg_fence(O); reg_fence(P);
  c.release(2);
  softmax_exp<false, PRO_SPLIT, 16>(S, z);
  pack_p(P, S);
  #pragma unroll 1
  for (int i = 0; i < 4; i++) {
    const uint32_t ph = i & 1;
    APROF(0);
    if (i > 0) fast_step<false, 1, 2>(S, O, P, Q, z, c, ph, ph, ph, i == 1);
    APROF(1);
    if (i == 3) break;
    if (i == 1) fast_step<true, 3, 0>(S, O, P, Q, z, c, 1, 0, 1, false);
    else        fast_step<false, 3, 0>(S, O, P, Q, z, c, 0, 1, 1, false);
  }
}

__device__ __forceinline__ void safe_heads(float (&S)[64], float (&O)[64], uint32_t (&P)[32], uint32_t (&Q)[32], SmState& z, Ctx& c) {
  first_qk(S, O, Q, c);
  wg_wait<0>();
  reg_fence(O); reg_fence(S);
  c.release(0);
  c.release(1);
  softmax_max<true>(O, z);
  exp_pack<true>(O, P, z);
  reg_fence(P);
  first_pv(O, P, c);
  wg_wait<0>();
  reg_fence(O); reg_fence(P);
  c.release(2);
  #pragma unroll 1
  for (int t = 1; t < 8; t++) {
    if (t > 1) {
      const int sk = (2 * t - 1) & 3, sv = (2 * t) & 3;
      mbar_wait(c.full0 + sk * 8, ((2 * t - 1) >> 2) & 1);
      mbar_wait(c.full0 + sv * 8, (t >> 1) & 1);
      ATT_SYNC(c.w);
      wg_fence();
      issue_qk(S, Q, c.base + sk * STAGE_BYTES + A_BYTES);
      issue_pv<true>(O, P, c.base + sv * STAGE_BYTES + A_BYTES, t != 5);
      ATT_ARRIVE(c.w);
      wg_wait<0>();
      reg_fence(S); reg_fence(O); reg_fence(P);
      c.release(sk);
      c.release(sv);
      reload_q(Q, c, t == 3);
      if (t == 4) {
        float i0, i1;
        row_inverse(z, i0, i1);
        z.m0 = -INFINITY; z.m1 = -INFINITY; z.l0 = 0.f; z.l1 = 0.f; z.k0 = 0.f; z.k1 = 0.f;
        stg_acquire(c);
        o_write(O, i0, i1, c);
        stg_publish(c);
      }
    }
    softmax_max<true>(S, z);
    softmax_exp<true, 0, 16>(S, z);
    #pragma unroll
    for (int j = 0; j < 16; j++) { O[4 * j] *= z.a0; O[4 * j + 1] *= z.a0; O[4 * j + 2] *= z.a1; O[4 * j + 3] *= z.a1; }
    pack_p(P, S);
  }
}

constexpr float SM_BOUND = 48.f;

__device__ __forceinline__ bool stash_and_vote(const float (&acc)[128], const uint32_t (&Q)[32], float qlim, const Ctx& c) {
  uint32_t n[8] = {0, 0, 0, 0, 0, 0, 0, 0};
  const uint32_t stash = stash_addr(c);
  #pragma unroll
  for (int v = 0; v < 8; v++) {
    uint32_t r[4];
    #pragma unroll
    for (int e = 0; e < 4; e++) {
      r[e] = pack_bf16(acc[64 + 8 * v + 2 * e], acc[65 + 8 * v + 2 * e]);
      n[4 + e] = bf2_fma(r[e], r[e], n[4 + e]);
      n[e] = bf2_fma(Q[4 * v + e], Q[4 * v + e], n[e]);
    }
    asm volatile("st.shared.v4.b32 [%0], {%1, %2, %3, %4};" :: "r"(stash + (v >> 2) * 8192 + (v & 3) * 512), "r"(r[0]), "r"(r[1]), "r"(r[2]), "r"(r[3]) : "memory");
  }
  const uint32_t m0 = bf2_add(n[0], n[2]), m1 = bf2_add(n[1], n[3]), m2 = bf2_add(n[4], n[6]), m3 = bf2_add(n[5], n[7]);
  const bool ok = (bf_lo(m0) + bf_hi(m0) <= qlim) && (bf_lo(m1) + bf_hi(m1) <= qlim) && (bf_lo(m2) + bf_hi(m2) <= qlim) && (bf_lo(m3) + bf_hi(m3) <= qlim);
  uint32_t all_ok;
  asm volatile("{\n.reg .pred p, q;\nsetp.ne.u32 q, %1, 0;\nbarrier.cta.red.and.aligned.pred p, %2, 128, q;\nselp.u32 %0, 1, 0, p;\n}"
    : "=r"(all_ok) : "r"((uint32_t)ok), "r"(3 + c.w) : "memory");
  return all_ok != 0;
}

__device__ __forceinline__ void attention_pair(float (&acc)[128], Ctx& c, uint32_t kvbar, bool last) {
  uint32_t Q[32];
  mbar_wait(kvbar, 0);
  stg_acquire(c);
  float qlim;
  asm volatile("ld.shared.f32 %0, [%1];" : "=f"(qlim) : "r"(kvbar + 8) : "memory");
  if (!last) {
    float m0, r0, m1, r1;
    const uint32_t t = tid_now();
    const uint32_t sa = c.base + SMEM_STAT + ((t >> 5) * 16 + ((t & 31) >> 2)) * 8, ca = c.base + SMEM_CS + (t & 3) * 8;
    asm volatile("ld.shared.v2.f32 {%0, %1}, [%2];" : "=f"(m0), "=f"(r0) : "r"(sa) : "memory");
    asm volatile("ld.shared.v2.f32 {%0, %1}, [%2];" : "=f"(m1), "=f"(r1) : "r"(sa + 64) : "memory");
    r0 *= SM_SCALE; r1 *= SM_SCALE; m0 *= -r0; m1 *= -r1;
    #pragma unroll
    for (int i = 0; i < 32; i++) {
      float c0, c1;
      asm volatile("ld.shared.v2.f32 {%0, %1}, [%2];" : "=f"(c0), "=f"(c1) : "r"(ca + i * 32) : "memory");
      acc[4 * i]     = fmaf(acc[4 * i],     r0, m0 * c0); acc[4 * i + 1] = fmaf(acc[4 * i + 1], r0, m0 * c1);
      acc[4 * i + 2] = fmaf(acc[4 * i + 2], r1, m1 * c0); acc[4 * i + 3] = fmaf(acc[4 * i + 3], r1, m1 * c1);
    }
  }
  float S[64], O[64];
  #pragma unroll
  for (int i = 0; i < 32; i++) Q[i] = pack_bf16(acc[2 * i], acc[2 * i + 1]);
  reg_fence(Q);
  const bool fast = stash_and_vote(acc, Q, qlim, c);
  BPROF(30);
  uint32_t P[32];
  SmState z{-INFINITY, -INFINITY, 0.f, 0.f, 0.f, 0.f, 1.f, 1.f};
  if (fast) fast_heads(S, O, P, Q, z, c, last);
  else      safe_heads(S, O, P, Q, z, c);
  mbar_wait(c.full0 + 24, 1);
  ATT_SYNC(c.w);
  BPROF(36);
  wg_fence();
  issue_pv<true>(O, P, c.base + 3 * STAGE_BYTES + A_BYTES, 1);
  ATT_ARRIVE(c.w);
  float i0, i1;
  row_inverse(z, i0, i1);
  stg_acquire(c);
  wg_wait<0>();
  reg_fence(O);
  c.release(3);
  BPROF(37);
  o_write(O, i0, i1, c);
  stg_publish(c);
}

template<int V0, int V1>
__device__ __forceinline__ void inbox_load(uint32_t (&r)[32], const uint4* p) {
  #pragma unroll
  for (int v = V0; v < V1; v++)
    asm volatile("ld.relaxed.gpu.global.v4.b32 {%0, %1, %2, %3}, [%4];" : "=r"(r[4 * v]), "=r"(r[4 * v + 1]), "=r"(r[4 * v + 2]), "=r"(r[4 * v + 3])
      : "l"(p + v * 256) : "memory");
}
template<int V0, int V1>
__device__ __forceinline__ bool inbox_missing(const uint32_t (&r)[32]) {
  uint32_t m = r[4 * V0];
  #pragma unroll
  for (int i = 4 * V0 + 1; i < 4 * V1; i++) m = min(m, r[i]);
  return __any_sync(0xffffffffu, m == 0);
}
template<int V0, int V1>
__device__ __forceinline__ void inbox_wait(uint32_t (&r)[32], const uint4* p, bool loaded) {
  if (loaded && !inbox_missing<V0, V1>(r)) return;
  #pragma unroll 1
  for (int it = 0; it < (1 << 21); it++) {
    inbox_load<V1 - 1, V1>(r, p);
    if (!inbox_missing<V1 - 1, V1>(r)) break;
  }
  #pragma unroll 1
  for (int it = 0; it < (1 << 21); it++) {
    inbox_load<V0, V1 - 1>(r, p);
    if (!inbox_missing<V0, V1 - 1>(r)) break;
  }
}
__device__ __forceinline__ uint32_t silu2(float y0, float y1, float nl2e) {
  const float a = 1.0f + ex2(fminf(y0 * nl2e, 60.f)), b = 1.0f + ex2(fminf(y1 * nl2e, 60.f));
  const float r = rcp(a * b);
  return pack_bf16(y0 * b * r, y1 * a * r);
}
template<bool TYPE_A>
__device__ __forceinline__ void final_combine(float (&acc)[128], const Ctx& c, const Pipe& p, uint4* outbox, const uint4* inbox,
                                              const CUtensorMap* out_map, int col, int row) {
  constexpr int KEEP = TYPE_A ? 0 : 64, SEND = 64 - KEEP;
  uint32_t G[32], R[32];
  const uint32_t t = tid_now(), sw0 = box_offset(t);
  const bool elect = (t & 127) == 0;
  mbar_wait(c.full0 + p.st * 8, p.ph);
  if (TYPE_A) inbox_load<0, 8>(R, inbox);
  float nl2e = -1.4426950408889634f;
  #pragma unroll
  for (int v = 0; v < 8; v++) {
    if (!TYPE_A && v == 8 - NG) asm volatile("ld.shared.f32 %0, [%1];" : "=f"(nl2e) : "r"(c.full0 + 200) : "memory");
    uint32_t r[4];
    #pragma unroll
    for (int e = 0; e < 4; e++) {
      const float lo = acc[SEND + 8 * v + 2 * e], hi = acc[SEND + 8 * v + 2 * e + 1];
      r[e] = (TYPE_A || v < 8 - NG) ? pack_bf16(lo, hi) : silu2(lo, hi, nl2e);
    }
    asm volatile("st.relaxed.gpu.global.v4.b32 [%0], {%1, %2, %3, %4};" :: "l"(outbox + v * 256), "r"(~r[0]), "r"(~r[1]), "r"(~r[2]), "r"(~r[3]) : "memory");
  }
  PROF(11);
  if (!TYPE_A) asm volatile("ld.shared.f32 %0, [%1];" : "=f"(nl2e) : "r"(c.full0 + 200) : "memory");
  #pragma unroll
  for (int i = 0; i < 32; i++) G[i] = TYPE_A ? pack_bf16(acc[2 * i], acc[2 * i + 1]) : silu2(acc[KEEP + 2 * i], acc[KEEP + 2 * i + 1], nl2e);
  if (!TYPE_A) { reg_fence(G); inbox_wait<0, 8>(R, inbox, false); }
  #pragma unroll
  for (int b = 0; b < 2; b++) {
    const uint32_t xa = c.base + p.st * STAGE_BYTES + b * 16384 + c.w * 8192;
    if (TYPE_A) { if (b == 0) inbox_wait<0, 4>(R, inbox, true); else inbox_wait<4, 8>(R, inbox, true); }
    if (b == 0) PROF(12);
    #pragma unroll
    for (int q = 0; q < 4; q++) {
      uint32_t xr[4];
      ldsm_x4((xa + sw0) ^ (q << 5), xr[0], xr[1], xr[2], xr[3]);
      #pragma unroll
      for (int e = 0; e < 4; e++) {
        const int i = b * 16 + q * 4 + e;
        uint32_t o = ~R[i];
        if (TYPE_A && i < (8 - NG) * 4) o = silu2(bf_lo(o), bf_hi(o), nl2e);
        xr[e] = bf2_add(xr[e], bf2_mul(o, G[i]));
      }
      stsm_x4((xa + sw0) ^ (q << 5), xr[0], xr[1], xr[2], xr[3]);
    }
    PROF(22 + 2 * b);
    fence_async_smem();
    asm volatile("bar.sync %0, 128;" :: "r"(3 + c.w) : "memory");
    if (elect) { tma_store_2d(out_map, xa, col + b * 64, row); bulk_commit(); }
    PROF(23 + 2 * b);
  }
  if (elect) bulk_wait_read0();
  PROF(13);
}

__global__ void __cluster_dims__(2, 1, 1) __launch_bounds__(384, 1)
fused_kernel(const __nv_bfloat16* __restrict__ x, const __nv_bfloat16* __restrict__ kc, const __nv_bfloat16* __restrict__ vc,
             const __grid_constant__ Maps maps) {
  extern __shared__ __align__(1024) uint8_t smem_raw[];
  const uint32_t base = smem_u32(smem_raw);
  const uint32_t bars = base + SMEM_BAR;
  const uint32_t full0 = bars, empty0 = bars + 32, sfull0 = bars + 64, sempty0 = bars + 80, kvbar = bars + 96, lnbar = bars + 112,
                 csbar = bars + 128, zbar = bars + 136;
  const int tid = threadIdx.x, lane = tid & 31;
  const int warp_id = __shfl_sync(0xffffffffu, tid >> 5, 0), wg = warp_id >> 2;
  const int rank = blockIdx.x & 1, rb = blockIdx.x & 15, j = blockIdx.x >> 4, jj = j & 3;
  const bool typeA = j < 4;
  const int row0 = rb * 128;
  const int kvrow = (j >> 1) * SK + (SK - WIN);

  if (warp_id != 8) asm volatile("barrier.cluster.arrive.relaxed.aligned;" ::: "memory");
  uint4 xv[2][4], kq, vq;
  if (wg < 2) {
    #pragma unroll
    for (int r = 0; r < 2; r++) {
      const uint4* src = reinterpret_cast<const uint4*>(x + (size_t)(row0 + j * 16 + warp_id * 2 + r) * D_MODEL);
      #pragma unroll
      for (int i = 0; i < 4; i++) xv[r][i] = __ldg(src + i * 32 + lane);
    }
    const size_t off = (size_t)(kvrow + ((j & 1) * 16 + rb) * 16 + warp_id * 2) * 128;
    kq = __ldg(reinterpret_cast<const uint4*>(kc + off) + lane);
    vq = __ldg(reinterpret_cast<const uint4*>(vc + off) + lane);
  }
  if (tid == 256) {
    for (int s = 0; s < NSTAGE; s++) { mbar_init(full0 + s * 8, 1); mbar_init(empty0 + s * 8, 4); }
    for (int s = 0; s < 2; s++) { mbar_init(sfull0 + s * 8, 4); mbar_init(sempty0 + s * 8, 1); }
    mbar_init(kvbar, 1); mbar_init(lnbar, 8); mbar_init(csbar, 1); mbar_init(zbar, 1);
    asm volatile("fence.mbarrier_init.release.cluster;" ::: "memory");
    fence_async_smem();
  }
  if (warp_id == 8) { __syncwarp(); asm volatile("barrier.cluster.arrive.relaxed.aligned;" ::: "memory"); }
  if (wg == 2) asm volatile("barrier.cluster.wait.aligned;" ::: "memory");
  if (tid == 256) {
    #pragma unroll 1
    for (int k = 0; k < NSTAGE; k++) {
      mbar_expect_tx(full0 + k * 8, STAGE_BYTES);
      tma_load_2d(base + k * STAGE_BYTES, &maps.x_ld, full0 + k * 8, k * 64, row0);
      tma_load_3d_mc(base + k * STAGE_BYTES + A_BYTES + rank * 16384, &maps.wq, full0 + k * 8, 0, k * 64 + rank * 32, j * 8);
    }
    mbar_expect_tx(csbar, 32768);
    #pragma unroll 1
    for (int k = 0; k < 4; k++) tma_load_2d(base + SMEM_STG + k * 8192, &maps.wq_cs, csbar, j * 512 + rb * 16, k * 256);
  }

  if (wg == 2) {
    asm volatile("setmaxnreg.dec.sync.aligned.u32 24;");
    unsigned done;
    asm volatile("ld.relaxed.gpu.global.u32 %0, [%1];" : "=r"(done) : "l"(g_flags + F_DONE * 32) : "memory");
    if (warp_id == 8) {
      if (lane == 0) {
        PPROF(4);
        Pipe p{0, 0};
        const int nseg = typeA ? 5 : 7;
        #pragma unroll 1
        for (int seg = 0; seg < nseg; seg++) {
          const CUtensorMap* ma = &maps.s_ld; const CUtensorMap* mb;
          int colA = C_XN, k0 = 0, kstep = 256, nk = 16, cg, flag = -1; unsigned cnt = 0; uint32_t bytes = STAGE_BYTES;
          if (seg < 2) {
            mb = &maps.wq; cg = j * 8 + seg * 4;
            if (seg == 0) { ma = &maps.x_ld; colA = 0; } else { colA = C_XQ; flag = F_LN + rb; cnt = 16; }
          } else if (seg < 4) {
            if (typeA) { mb = &maps.w1a; cg = jj * 6 + (seg - 2) * 3; bytes = A_BYTES + 24576; }
            else       { mb = &maps.w1b; cg = 24 + jj * 8 + (seg - 2) * 4; }
          } else {
            cg = jj * 4;
            if (typeA) { mb = &maps.wo; colA = C_O; nk = 64; flag = F_O + rb; cnt = 64; }
            else {
              mb = &maps.w2; colA = C_H;
              if (seg == 4)      { k0 = 1536; kstep = 512; flag = F_HB1 + rb; cnt = 16; }
              else if (seg == 5) { nk = 24; flag = F_HA + rb; cnt = 32; }
              else               { k0 = 1792; kstep = 512; flag = F_HB2 + rb; cnt = 16; }
            }
          }
          PPROF(20 + 2 * seg);
          if (flag >= 0) flag_wait(flag, (done / NCTA + 1) * cnt);
          PPROF(21 + 2 * seg);
          #pragma unroll 1
          for (int k = seg == 0 ? NSTAGE : 0; k < nk; k++) {
            const int kcol = k0 + (k >> 2) * kstep + (k & 3) * 64;
            const uint32_t sa = base + p.st * STAGE_BYTES, fb = full0 + p.st * 8;
            mbar_wait(empty0 + p.st * 8, p.ph);
            mbar_expect_tx(fb, bytes);
            tma_load_3d_mc(sa + A_BYTES + rank * 16384, mb, fb, 0, kcol + rank * 32, cg);
            tma_load_2d(sa, ma, fb, colA + kcol, row0);
            if (seg == nseg - 1 && k == nk - ZERO_LEAD) mbar_arrive(zbar);
            p.next();
          }
          if (seg < 2) {
            #pragma unroll 1
            for (int i = 0; i < 16; i++) {
              const bool isK = (i == 0) || ((i & 1) && i < 15);
              const int t = isK ? (i + 1) >> 1 : (i - 1) >> 1;
              mbar_wait(empty0 + p.st * 8, p.ph);
              const uint32_t sa = base + p.st * STAGE_BYTES, fb = full0 + p.st * 8;
              mbar_expect_tx(fb, 32768);
              tma_load_2d_mc(sa + A_BYTES + rank * 16384, isK ? &maps.k : &maps.v, fb, rank * 64, kvrow + (t & 3) * 128);
              p.next();
            }
          }
        }
        {
          const uint32_t sa = base + p.st * STAGE_BYTES, fb = full0 + p.st * 8;
          const int col = jj * 256 + (typeA ? 0 : 128);
          flag_wait(F_X + (blockIdx.x ^ 64), done / NCTA + 1);
          mbar_wait(empty0 + p.st * 8, p.ph);
          mbar_expect_tx(fb, 32768);
          tma_load_2d(sa, &maps.x_ld, fb, col, row0);
          tma_load_2d(sa + 16384, &maps.x_ld, fb, col + 64, row0);
        }
        asm volatile("red.relaxed.gpu.global.add.u32 [%0], 1;" :: "l"(g_flags + F_DONE * 32) : "memory");
      }
    } else if (warp_id <= 10) {
      const int w = warp_id - 9;
      {
        mbar_wait(csbar, 0);
        const uint32_t src = base + SMEM_STG + w * 16384 + lane * 16;
        float a[8] = {0.f, 0.f, 0.f, 0.f, 0.f, 0.f, 0.f, 0.f};
        #pragma unroll 4
        for (int r = 0; r < 32; r++) {
          uint32_t v0, v1, v2, v3;
          asm volatile("ld.shared.v4.b32 {%0, %1, %2, %3}, [%4];" : "=r"(v0), "=r"(v1), "=r"(v2), "=r"(v3) : "r"(src + r * 512));
          a[0] += bf_lo(v0); a[1] += bf_hi(v0); a[2] += bf_lo(v1); a[3] += bf_hi(v1);
          a[4] += bf_lo(v2); a[5] += bf_hi(v2); a[6] += bf_lo(v3); a[7] += bf_hi(v3);
        }
        #pragma unroll 1
        for (int o = 2; o < 32; o <<= 1) {
          #pragma unroll
          for (int i = 0; i < 8; i++) a[i] += __shfl_xor_sync(0xffffffffu, a[i], o);
        }
        if (lane < 2) {
          asm volatile("st.shared.v4.f32 [%0], {%1, %2, %3, %4};" :: "r"(base + SMEM_CS + w * 64 + lane * 32), "f"(a[0]), "f"(a[1]), "f"(a[2]), "f"(a[3]) : "memory");
          asm volatile("st.shared.v4.f32 [%0], {%1, %2, %3, %4};" :: "r"(base + SMEM_CS + w * 64 + lane * 32 + 16), "f"(a[4]), "f"(a[5]), "f"(a[6]), "f"(a[7]) : "memory");
        }
        asm volatile("bar.arrive 5, 96;" ::: "memory");
        asm volatile("bar.sync 6, 96;" ::: "memory");
        #pragma unroll 1
        for (int r = w * 8; r < w * 8 + 8; r++) {
          const size_t row = row0 + j * 16 + r;
          const uint4* xs = reinterpret_cast<const uint4*>(x + row * D_MODEL) + lane;
          uint4* dst = reinterpret_cast<uint4*>(g_scratch + row * S_COLS) + lane;
          uint4 v[4];
          #pragma unroll
          for (int i = 0; i < 4; i++) v[i] = __ldg(xs + i * 32);
          float mean, inv;
          asm volatile("ld.shared.v2.f32 {%0, %1}, [%2];" : "=f"(mean), "=f"(inv) : "r"(base + SMEM_OWN + r * 8) : "memory");
          const uint32_t mb = pack_bf16(mean, mean);
          const float invq = inv * SM_SCALE;
          #pragma unroll
          for (int i = 0; i < 4; i++) {
            const uint32_t d0 = bf2_sub(v[i].x, mb), d1 = bf2_sub(v[i].y, mb), d2 = bf2_sub(v[i].z, mb), d3 = bf2_sub(v[i].w, mb);
            dst[C_XN / 8 + i * 32] = make_uint4(pack_bf16(bf_lo(d0) * inv, bf_hi(d0) * inv), pack_bf16(bf_lo(d1) * inv, bf_hi(d1) * inv),
                                                pack_bf16(bf_lo(d2) * inv, bf_hi(d2) * inv), pack_bf16(bf_lo(d3) * inv, bf_hi(d3) * inv));
            dst[C_XQ / 8 + i * 32] = make_uint4(pack_bf16(bf_lo(d0) * invq, bf_hi(d0) * invq), pack_bf16(bf_lo(d1) * invq, bf_hi(d1) * invq),
                                                pack_bf16(bf_lo(d2) * invq, bf_hi(d2) * invq), pack_bf16(bf_lo(d3) * invq, bf_hi(d3) * invq));
          }
        }
        __syncwarp();
      }
      if (lane == 0) {
        flag_signal(F_LN + rb);
        HPROF(5 + w);
        const uint32_t sfull = sfull0 + w * 8, sempty = sempty0 + w * 8, stg = base + SMEM_STG + w * 16384;
        const int row = row0 + w * 64;
        #pragma unroll 1
        for (int job = 0; job < 8; job++) {
          int col, nb = 2, flag;
          if (job < 4) { col = C_O + (j * 4 + job) * 128; flag = F_O + rb; }
          else {
            const int t = (job - 4) >> 1, part = job & 1;
            if (typeA) { col = C_H + jj * 384 + t * 192 + part * 128; nb = 2 - part; flag = F_HA + rb; }
            else       { col = C_H + 1536 + jj * 512 + t * 256 + part * 128; flag = (t == 0 ? F_HB1 : F_HB2) + rb; }
          }
          mbar_wait(sfull, job & 1);
          #pragma unroll 1
          for (int b = 0; b < nb; b++) {
            tma_store_2d(&maps.s_st, stg + b * 8192, col + b * 64, row);
            bulk_commit();
            bulk_wait_read0();
          }
          mbar_arrive(sempty);
          bulk_wait0();
          HPROF(36 + w * 8 + job);
          flag_signal(flag);
        }
      }
    } else {
      if (lane < 12) asm volatile("prefetch.tensormap [%0];" :: "l"(&maps.s_ld + lane) : "memory");
      const unsigned ep = done / NCTA + 1;
      HPROF(8);
      mbar_wait(lnbar, 0);
      if (lane < 16) {
        float2 st;
        asm volatile("ld.shared.v2.f32 {%0, %1}, [%2];" : "=f"(st.x), "=f"(st.y) : "r"(base + SMEM_OWN + lane * 8) : "memory");
        g_sync.stats[row0 + j * 16 + lane] = st;
      }
      {
        uint32_t m;
        asm volatile("ld.shared.u32 %0, [%1];" : "=r"(m) : "r"(base + SMEM_OWN + 128 + (lane & 15) * 4) : "memory");
        #pragma unroll
        for (int o = 2; o < 16; o <<= 1) m = max(m, __shfl_xor_sync(0xffffffffu, m, o));
        if (lane < 2)
          asm volatile("red.relaxed.gpu.global.max.u64 [%0], %1;" :: "l"(g_sync.kvmax + (j >> 1) * 32 + lane * 16), "l"(((unsigned long long)ep << 32) | m) : "memory");
      }
      asm volatile("bar.sync 5, 96;" ::: "memory");
      HPROF(9);
      if (lane < 16) {
        float u, v;
        asm volatile("ld.shared.f32 %0, [%1];" : "=f"(u) : "r"(base + SMEM_CS + lane * 4) : "memory");
        asm volatile("ld.shared.f32 %0, [%1];" : "=f"(v) : "r"(base + SMEM_CS + 64 + lane * 4) : "memory");
        g_sync.colsum[j * 256 + rb * 16 + lane] = u + v;
      }
      __syncwarp();
      unsigned* const fl = g_flags + (lane == 0 ? F_ST + rb : lane == 1 ? F_CS + j : F_KV + (j >> 1)) * 32;
      if (lane < 3) {
        HPROF(12);
        asm volatile("red.release.gpu.global.add.u32 [%0], 1;" :: "l"(fl) : "memory");
        HPROF(13);
      }
      __syncwarp();
      asm volatile("bar.arrive 6, 96;" ::: "memory");
      if (lane < 3) {
        asm volatile("{\n.reg .pred p;\n.reg .u32 c, v;\nmov.u32 c, 0;\n"
          "WAIT:\n"
          "ld.acquire.gpu.global.u32 v, [%0];\n"
          "sub.u32 v, v, %1;\n"
          "setp.ge.s32 p, v, 0;\n"
          "@p bra DONE;\n"
          "add.u32 c, c, 1;\n"
          "setp.gt.u32 p, c, 0x400000;\n"
          "@p trap;\n"
          "bra WAIT;\n"
          "DONE:\n}" :: "l"(fl), "r"(ep * (8u << lane)) : "memory");
      }
      __syncwarp();
      HPROF(11);
      const float4 s0 = __ldcg(reinterpret_cast<const float4*>(g_sync.stats + row0) + lane), s1 = __ldcg(reinterpret_cast<const float4*>(g_sync.stats + row0) + 32 + lane);
      const float4 c0 = __ldcg(reinterpret_cast<const float4*>(g_sync.colsum + j * 256) + lane), c1 = __ldcg(reinterpret_cast<const float4*>(g_sync.colsum + j * 256) + 32 + lane);
      const float k2 = __uint_as_float((unsigned)__ldcg(g_sync.kvmax + (j >> 1) * 32)), va = __uint_as_float((unsigned)__ldcg(g_sync.kvmax + (j >> 1) * 32 + 16));
      asm volatile("st.shared.v4.f32 [%0], {%1, %2, %3, %4};" :: "r"(base + SMEM_STAT + lane * 16), "f"(s0.x), "f"(s0.y), "f"(s0.z), "f"(s0.w) : "memory");
      asm volatile("st.shared.v4.f32 [%0], {%1, %2, %3, %4};" :: "r"(base + SMEM_STAT + 512 + lane * 16), "f"(s1.x), "f"(s1.y), "f"(s1.z), "f"(s1.w) : "memory");
      asm volatile("st.shared.v4.f32 [%0], {%1, %2, %3, %4};" :: "r"(base + SMEM_CS + lane * 16), "f"(c0.x), "f"(c0.y), "f"(c0.z), "f"(c0.w) : "memory");
      asm volatile("st.shared.v4.f32 [%0], {%1, %2, %3, %4};" :: "r"(base + SMEM_CS + 512 + lane * 16), "f"(c1.x), "f"(c1.y), "f"(c1.z), "f"(c1.w) : "memory");
      __syncwarp();
      if (lane == 0) {
        float qlim = __fdividef(SM_BOUND * SM_BOUND * 0.25f * 0.9f, k2);
        if (!(va >= 0x1p-50f && va <= 0x1p60f) || !(k2 <= 0x1p120f)) qlim = -1.f;
        asm volatile("st.shared.f32 [%0], %1;" :: "r"(kvbar + 8), "f"(qlim) : "memory");
        asm volatile("st.shared.f32 [%0], %1;" :: "r"(bars + 200), "f"(-1.4426950408889634f) : "memory");
        mbar_arrive(kvbar);
        HPROF(7);
      }
      mbar_wait(zbar, 0);
      if (lane < 2) asm volatile("prefetch.tensormap [%0];" :: "l"(&maps.x_ld + lane) : "memory");
      #pragma unroll 4
      for (int i = 0; i < 64; i++)
        g_xch[((rb * 4 + jj) * 2 + (j >> 2)) * 2048 + i * 32 + lane] = make_uint4(0, 0, 0, 0);
      __syncwarp();
      if (lane == 0) flag_signal(F_X + blockIdx.x);
      HPROF(14);
    }
  } else {
    PROF(0);
    {
      float s[2], q[2];
      #pragma unroll
      for (int r = 0; r < 2; r++) {
        const uint32_t* u = reinterpret_cast<const uint32_t*>(xv[r]);
        float a = 0.f, b = 0.f;
        #pragma unroll
        for (int i = 0; i < 16; i++) { a += bf_lo(u[i]); b += bf_hi(u[i]); }
        s[r] = a + b;
      }
      #pragma unroll
      for (int o = 16; o > 0; o >>= 1) { s[0] += __shfl_xor_sync(0xffffffffu, s[0], o); s[1] += __shfl_xor_sync(0xffffffffu, s[1], o); }
      #pragma unroll
      for (int r = 0; r < 2; r++) {
        const uint32_t* u = reinterpret_cast<const uint32_t*>(xv[r]);
        s[r] *= (1.0f / D_MODEL);
        float a = 0.f, b = 0.f;
        #pragma unroll
        for (int i = 0; i < 16; i++) { const float d = bf_lo(u[i]) - s[r], e = bf_hi(u[i]) - s[r]; a = fmaf(d, d, a); b = fmaf(e, e, b); }
        q[r] = a + b;
      }
      #pragma unroll
      for (int o = 16; o > 0; o >>= 1) { q[0] += __shfl_xor_sync(0xffffffffu, q[0], o); q[1] += __shfl_xor_sync(0xffffffffu, q[1], o); }
      const uint32_t ku[4] = {kq.x, kq.y, kq.z, kq.w}, vu[4] = {vq.x, vq.y, vq.z, vq.w};
      float k2 = 0.f; uint32_t vm = 0;
      #pragma unroll
      for (int i = 0; i < 4; i++) {
        k2 = fmaf(bf_lo(ku[i]), bf_lo(ku[i]), k2); k2 = fmaf(bf_hi(ku[i]), bf_hi(ku[i]), k2);
        vm = max(vm, max((vu[i] << 16) & 0x7fffffffu, vu[i] & 0x7fff0000u));
      }
      #pragma unroll
      for (int o = 8; o > 0; o >>= 1) k2 += __shfl_xor_sync(0xffffffffu, k2, o);
      const uint32_t k2m = __reduce_max_sync(0xffffffffu, __float_as_uint(k2) & 0x7fffffffu);
      vm = __reduce_max_sync(0xffffffffu, vm);
      asm volatile("barrier.cluster.wait.aligned;" ::: "memory");
      if (lane == 0) {
        asm volatile("st.shared.v2.u32 [%0], {%1, %2};" :: "r"(base + SMEM_OWN + 128 + warp_id * 8), "r"(k2m), "r"(vm) : "memory");
        #pragma unroll
        for (int r = 0; r < 2; r++) {
          float den;
          asm("sqrt.approx.f32 %0, %1;" : "=f"(den) : "f"(round_bf16(round_bf16(q[r] * (1.0f / D_MODEL)) + 1e-5f)));
          asm volatile("st.shared.v2.f32 [%0], {%1, %2};" :: "r"(base + SMEM_OWN + (warp_id * 2 + r) * 8), "f"(round_bf16(s[r])), "f"(rcp(round_bf16(den))) : "memory");
        }
        mbar_arrive(lnbar);
      }
    }
    PROF(1);
    asm volatile("setmaxnreg.inc.sync.aligned.u32 240;");

    Ctx c;
    c.base = base; c.full0 = full0; c.sfull = sfull0 + wg * 8; c.sempty = sempty0 + wg * 8;
    c.stg = base + SMEM_STG + wg * 16384; c.w = wg;
    c.stgw = c.stg + box_offset(tid);
    c.njob = 0; c.rel = (tid & 95) == 0;
    asm("mapa.shared::cluster.u32 %0, %1, %2;" : "=r"(c.relbar) : "r"(empty0), "r"((tid >> 5) & 1));
    Pipe p{0, 0};
    if (wg == 1) turn_arrive(1);
    float acc[128];
    uint32_t held[32];
    #pragma unroll 1
    do {
      gemm_tile<256, false>(acc, held, c, p, 16, false, false);
      PROF(2 + c.njob);
      attention_pair(acc, c, kvbar, c.njob != 0);
      PROF(1 + c.njob);
    } while (c.njob < 4);
    if (typeA) {
      gemm_tile<192, false>(acc, held, c, p, 16, false, false);
      PROF(6);
      epi_relu<16>(acc, held, c);
      PROF(7);
      gemm_tile<192, true>(acc, held, c, p, 16, true, false);
      PROF(8);
      epi_relu<16>(acc, held, c);
      PROF(9);
      gemm_tile<256, true>(acc, held, c, p, 64, true, true);
      PROF(10);
      final_combine<true>(acc, c, p, g_xch + (rb * 4 + jj) * 4096 + 2048 + tid_now(), g_xch + (rb * 4 + jj) * 4096 + tid_now(), &maps.out_st, jj * 256, row0 + wg * 64);
    } else {
      gemm_tile<256, false>(acc, held, c, p, 16, false, false);
      #pragma unroll 1
      while (true) {
        PROF(c.njob + 2);
        epi_relu<32>(acc, held, c);
        PROF(c.njob + 2);
        const bool fin = c.njob == 7;
        gemm_tile<256, true>(acc, held, c, p, fin ? 56 : 16, true, fin);
        if (fin) break;
      }
      PROF(10);
      final_combine<false>(acc, c, p, g_xch + (rb * 4 + jj) * 4096 + tid_now(), g_xch + (rb * 4 + jj) * 4096 + 2048 + tid_now(), &maps.out_st, jj * 256 + 128, row0 + wg * 64);
    }
    if (wg == 0) turn_sync(0);
  }
}

typedef CUresult (*EncodeFn)(CUtensorMap*, CUtensorMapDataType, cuuint32_t, void*, const cuuint64_t*, const cuuint64_t*, const cuuint32_t*,
                             const cuuint32_t*, CUtensorMapInterleave, CUtensorMapSwizzle, CUtensorMapL2promotion, CUtensorMapFloatOOBfill);

void map2d(EncodeFn enc, CUtensorMap* m, const void* p, uint64_t rows, uint64_t cols, uint32_t box_rows) {
  cuuint64_t dims[2] = {cols, rows}; cuuint64_t strides[1] = {cols * 2};
  cuuint32_t box[2] = {64, box_rows}; cuuint32_t es[2] = {1, 1};
  enc(m, CU_TENSOR_MAP_DATA_TYPE_BFLOAT16, 2, const_cast<void*>(p), dims, strides, box, es, CU_TENSOR_MAP_INTERLEAVE_NONE,
      CU_TENSOR_MAP_SWIZZLE_128B, CU_TENSOR_MAP_L2_PROMOTION_L2_256B, CU_TENSOR_MAP_FLOAT_OOB_FILL_NONE);
}
void map3d(EncodeFn enc, CUtensorMap* m, const void* p, uint64_t rows, uint64_t cols, uint32_t box_rows, uint32_t groups) {
  cuuint64_t dims[3] = {64, rows, cols / 64}; cuuint64_t strides[2] = {cols * 2, 128};
  cuuint32_t box[3] = {64, box_rows, groups}; cuuint32_t es[3] = {1, 1, 1};
  enc(m, CU_TENSOR_MAP_DATA_TYPE_BFLOAT16, 3, const_cast<void*>(p), dims, strides, box, es, CU_TENSOR_MAP_INTERLEAVE_NONE,
      CU_TENSOR_MAP_SWIZZLE_128B, CU_TENSOR_MAP_L2_PROMOTION_L2_256B, CU_TENSOR_MAP_FLOAT_OOB_FILL_NONE);
}

void map_cs(EncodeFn enc, CUtensorMap* m, const void* p) {
  cuuint64_t dims[2] = {4096, D_MODEL}; cuuint64_t strides[1] = {4096 * 2};
  cuuint32_t box[2] = {16, 256}; cuuint32_t es[2] = {1, 1};
  enc(m, CU_TENSOR_MAP_DATA_TYPE_BFLOAT16, 2, const_cast<void*>(p), dims, strides, box, es, CU_TENSOR_MAP_INTERLEAVE_NONE,
      CU_TENSOR_MAP_SWIZZLE_NONE, CU_TENSOR_MAP_L2_PROMOTION_L2_128B, CU_TENSOR_MAP_FLOAT_OOB_FILL_NONE);
}

}

extern "C" void kernel_launch(void* const* d_in, const int* in_sizes, int n_in, void* d_out, int out_size) {
  (void)in_sizes; (void)n_in; (void)out_size;
  static EncodeFn enc = nullptr;
  static void* scratch = nullptr;
  if (!enc) {
    void* fn = nullptr; cudaDriverEntryPointQueryResult st;
    cudaGetDriverEntryPoint("cuTensorMapEncodeTiled", &fn, cudaEnableDefault, &st);
    enc = (EncodeFn)fn;
    cudaGetSymbolAddress(&scratch, g_scratch);
    cudaFuncSetAttribute(fused_kernel, cudaFuncAttributeMaxDynamicSharedMemorySize, SMEM_TOTAL + PROF_SMEM);
  }
  Maps m;
  map2d(enc, &m.s_ld, scratch, S_ROWS, S_COLS, 128);
  map2d(enc, &m.s_st, scratch, S_ROWS, S_COLS, 64);
  map3d(enc, &m.wq, d_in[3], D_MODEL, 4096, 32, 4);
  map3d(enc, &m.w1a, d_in[6], D_MODEL, DFF, 32, 3);
  map3d(enc, &m.w1b, d_in[6], D_MODEL, DFF, 32, 4);
  map3d(enc, &m.wo, d_in[4], 4096, D_MODEL, 32, 4);
  map3d(enc, &m.w2, d_in[7], DFF, D_MODEL, 32, 4);
  map2d(enc, &m.k, d_in[1], 4 * SK, 128, 128);
  map2d(enc, &m.v, d_in[2], 4 * SK, 128, 128);
  map2d(enc, &m.x_ld, d_in[0], S_ROWS, D_MODEL, 128);
  map2d(enc, &m.out_st, d_out, S_ROWS, D_MODEL, 64);
  map_cs(enc, &m.wq_cs, d_in[3]);
  fused_kernel<<<NCTA, 384, SMEM_TOTAL + PROF_SMEM>>>((const __nv_bfloat16*)d_in[0], (const __nv_bfloat16*)d_in[1], (const __nv_bfloat16*)d_in[2], m);
}
```
